```python
import torch

def _softmax(x, axis=-1):
    return torch.softmax(x, dim=axis)
def _gelu(x):
    return torch.nn.functional.gelu(x, approximate="tanh")
def _silu(x):
    return torch.nn.functional.silu(x)
def _sigmoid(x):
    return torch.sigmoid(x)
def _layernorm(x, axis=-1, eps=1e-5):
    m = x.mean(dim=axis, keepdim=True)
    v = x.var(dim=axis, keepdim=True, unbiased=False)
    return (x - m) / torch.sqrt(v + eps)
def _scatter_add(tgt, idx, src, axis=0):
    return tgt.clone().index_add_(axis, idx, src)
def _segment_sum(src, seg, n):
    out = torch.zeros((n,) + src.shape[1:], dtype=src.dtype)
    return out.index_add_(0, seg, src)
def _pad(x, pw):
    flat = tuple(v for pair in reversed(pw) for v in pair)
    return torch.nn.functional.pad(x, flat)

kernel_name = 'concat_heads__mha_block_cached__gqa_block_cached__near_ridge'

def setup_inputs():

    _w = (lambda a: (lambda t: t.to(torch.bfloat16) if t.is_floating_point() else t)(torch.as_tensor(a)))
    def _A_setup():
        B, Sq, D = 8, 128, 640
        H, Sk, Dh = 32, 1024, 192
        return {
            "x": _w((lambda *s: torch.randn(*s, dtype=torch.bfloat16) * 0.8)(B, Sq, D)),
            "k_cache": _w((lambda *s: torch.randn(*s, dtype=torch.bfloat16) * 0.8)(B, H, Sk, Dh)),
            "v_cache": _w((lambda *s: torch.randn(*s, dtype=torch.bfloat16) * 0.05)(B, H, Sk, Dh)),
            "wq": _w((lambda *s: torch.randn(*s, dtype=torch.bfloat16) * 0.8)(D, H * Dh) * (D ** -0.5)),
            "wo": _w((lambda *s: torch.randn(*s, dtype=torch.bfloat16) * 0.05)(H * Dh, D) * ((H * Dh) ** -0.5)),
        }
    _A_in = _A_setup()

    def _B_setup():
        B, Sq, D = 8, 128, 640
        Hq, Hkv, Sk, Dh = 32, 32, 1024, 192
        assert Hq % Hkv == 0, (Hq, Hkv)
        return {
            "x": _w((lambda *s: torch.randn(*s, dtype=torch.bfloat16) * 0.8)(B, Sq, D)),
            "k_cache": _w((lambda *s: torch.randn(*s, dtype=torch.bfloat16) * 0.8)(B, Hkv, Sk, Dh)),
            "v_cache": _w((lambda *s: torch.randn(*s, dtype=torch.bfloat16) * 0.05)(B, Hkv, Sk, Dh)),
            "wq": _w((lambda *s: torch.randn(*s, dtype=torch.bfloat16) * 0.8)(D, Hq * Dh) * (D ** -0.5)),
            "wo": _w((lambda *s: torch.randn(*s, dtype=torch.bfloat16) * 0.05)(Hq * Dh, D) * ((Hq * Dh) ** -0.5)),
        }
    _B_in = _B_setup()

    return {
        "A_x": _A_in["x"],
        "A_k_cache": _A_in["k_cache"],
        "A_v_cache": _A_in["v_cache"],
        "A_wq": _A_in["wq"],
        "A_wo": _A_in["wo"],
        "B_x": _B_in["x"],
        "B_k_cache": _B_in["k_cache"],
        "B_v_cache": _B_in["v_cache"],
        "B_wq": _B_in["wq"],
        "B_wo": _B_in["wo"],
    }

def reference(A_x, A_k_cache, A_v_cache, A_wq, A_wo, B_x, B_k_cache, B_v_cache, B_wq, B_wo):
    def _A_ref(x, k_cache, v_cache, wq, wo):
        B, Sq, D = x.shape
        H, Dh = 32, 192
        q = (lambda x, *d: x.permute(*d))((x @ wq).reshape(B, Sq, H, Dh), 0, 2, 1, 3)
        scores = torch.einsum("bhqd,bhkd->bhqk", q, k_cache) * (Dh ** -0.5)
        p = _softmax(scores, axis=-1)
        o = torch.einsum("bhqk,bhkd->bhqd", p, v_cache)
        return (lambda x, *d: x.permute(*d))(o, 0, 2, 1, 3).reshape(B, Sq, H * Dh) @ wo

    def _B_ref(x, k_cache, v_cache, wq, wo):
        B, Sq, D = x.shape
        Hq, Dh = 32, 192
        Hkv = k_cache.shape[1]
        rep = Hq // Hkv
        q = (lambda x, *d: x.permute(*d))((x @ wq).reshape(B, Sq, Hq, Dh), 0, 2, 1, 3)
        k = (lambda x, n, axis: torch.repeat_interleave(x, n, dim=axis))(k_cache, rep, axis=1)
        v = (lambda x, n, axis: torch.repeat_interleave(x, n, dim=axis))(v_cache, rep, axis=1)
        scores = torch.einsum("bhqd,bhkd->bhqk", q, k) * (Dh ** -0.5)
        p = _softmax(scores, axis=-1)
        o = torch.einsum("bhqk,bhkd->bhqd", p, v)
        return (lambda x, *d: x.permute(*d))(o, 0, 2, 1, 3).reshape(B, Sq, Hq * Dh) @ wo

    a = _A_ref(A_x, A_k_cache, A_v_cache, A_wq, A_wo)
    b = _B_ref(B_x, B_k_cache, B_v_cache, B_wq, B_wo)
    return torch.concatenate([a, b], axis=-1)
```

```cpp
#include <cuda_runtime.h>
#include <cuda.h>
#include <cuda_bf16.h>
#include <stdint.h>

namespace {

constexpr int kItems   = 512;
constexpr int kNumOp   = 32;
constexpr int kMaxCtas = 160;
constexpr int kStages  = 4;
constexpr int kAttSlot = 49152;
constexpr int kOpSlot  = 57344;
constexpr int kSmemBytes = kStages * kOpSlot + 1024;
constexpr int kThreads = 384;

struct Maps { CUtensorMap k[2], v[2], x[2], wq[2], wo[2]; };
struct Params {
  const __nv_bfloat16* k[2];
  const __nv_bfloat16* v[2];
  const __nv_bfloat16* wo[2];
  __nv_bfloat16* out;
  int qstag, win, late, pf0, pftau, wpf;
};

__device__ uint4 g_obuf[kMaxCtas * 3072];
struct Sync { int next; int pad0[31]; int done; int pad1[31]; int flag[16 * 32]; int consumed[kMaxCtas]; };
__device__ Sync g_sync;

__device__ __forceinline__ uint32_t smem_u32(const void* p) { return (uint32_t)__cvta_generic_to_shared(p); }
__device__ __forceinline__ void mbar_init(uint32_t b, uint32_t c) { asm volatile("mbarrier.init.shared::cta.b64 [%0], %1;" ::"r"(b), "r"(c)); }
__device__ __forceinline__ void mbar_expect(uint32_t b, uint32_t bytes) { asm volatile("mbarrier.arrive.expect_tx.shared::cta.b64 _, [%0], %1;" ::"r"(b), "r"(bytes) : "memory"); }
__device__ __forceinline__ void mbar_arrive(uint32_t b) { asm volatile("mbarrier.arrive.shared::cta.b64 _, [%0];" ::"r"(b) : "memory"); }
__device__ __forceinline__ bool mbar_try(uint32_t b, uint32_t ph) {
  uint32_t ok;
  asm volatile("{\n.reg .pred p;\nmbarrier.try_wait.parity.shared::cta.b64 p, [%1], %2;\nselp.u32 %0, 1, 0, p;\n}" : "=r"(ok) : "r"(b), "r"(ph) : "memory");
  return ok;
}
__device__ __forceinline__ void mbar_wait(uint32_t b, uint32_t ph) {
  if (mbar_try(b, ph)) return;
#pragma unroll 1
  for (int i = 0; i < (1 << 22); i++) if (mbar_try(b, ph)) return;
  __trap();
}
__device__ __forceinline__ uint32_t clk32() { uint32_t c; asm volatile("mov.u32 %0, %%clock;" : "=r"(c)); return c; }
__device__ __forceinline__ void tma3(uint32_t dst, const CUtensorMap* m, uint32_t bar, int c0, int c1, int c2, uint64_t pol) {
  asm volatile("cp.async.bulk.tensor.3d.shared::cluster.global.mbarrier::complete_tx::bytes.L2::cache_hint [%0], [%1, {%3, %4, %5}], [%2], %6;"
               ::"r"(dst), "l"(m), "r"(bar), "r"(c0), "r"(c1), "r"(c2), "l"(pol) : "memory");
}
__device__ __forceinline__ void tma3n(uint32_t dst, const CUtensorMap* m, uint32_t bar, int c0, int c1, int c2) {
  asm volatile("cp.async.bulk.tensor.3d.shared::cluster.global.mbarrier::complete_tx::bytes [%0], [%1, {%3, %4, %5}], [%2];"
               ::"r"(dst), "l"(m), "r"(bar), "r"(c0), "r"(c1), "r"(c2) : "memory");
}
__device__ __forceinline__ void tma2n(uint32_t dst, const CUtensorMap* m, uint32_t bar, int c0, int c1) {
  asm volatile("cp.async.bulk.tensor.2d.shared::cluster.global.mbarrier::complete_tx::bytes [%0], [%1, {%3, %4}], [%2];"
               ::"r"(dst), "l"(m), "r"(bar), "r"(c0), "r"(c1) : "memory");
}
__device__ __forceinline__ void bulk_g2s(uint32_t dst, const void* src, uint32_t bytes, uint32_t bar) {
  asm volatile("cp.async.bulk.shared::cluster.global.mbarrier::complete_tx::bytes [%0], [%1], %2, [%3];"
               ::"r"(dst), "l"(src), "r"(bytes), "r"(bar) : "memory");
}
__device__ __forceinline__ void l2_prefetch(const void* src, uint32_t bytes) {
  asm volatile("cp.async.bulk.prefetch.L2.global [%0], %1;" ::"l"(src), "r"(bytes) : "memory");
}
__device__ __forceinline__ void l2_prefetch_pol(const void* src, uint32_t bytes, uint64_t pol) {
  asm volatile("cp.async.bulk.prefetch.L2.global.L2::cache_hint [%0], %1, %2;" ::"l"(src), "r"(bytes), "l"(pol) : "memory");
}
__device__ __forceinline__ void l2_prefetch_t3(const CUtensorMap* m, int c0, int c1, int c2) {
  asm volatile("cp.async.bulk.prefetch.tensor.3d.L2.global.tile [%0, {%1, %2, %3}];" ::"l"(m), "r"(c0), "r"(c1), "r"(c2) : "memory");
}
__device__ __forceinline__ void tmap_prefetch(const CUtensorMap* m) { asm volatile("prefetch.tensormap [%0];" ::"l"(m) : "memory"); }
__device__ __forceinline__ int ld_acquire(const int* p) { int v; asm volatile("ld.acquire.gpu.global.s32 %0, [%1];" : "=r"(v) : "l"(p) : "memory"); return v; }
__device__ __forceinline__ void st_relaxed(int* p, int v) { asm volatile("st.relaxed.gpu.global.s32 [%0], %1;" ::"l"(p), "r"(v) : "memory"); }
__device__ __forceinline__ void red_add_relaxed(int* p, int v) { asm volatile("red.relaxed.gpu.global.add.s32 [%0], %1;" ::"l"(p), "r"(v) : "memory"); }
__device__ __forceinline__ void fence_gpu() { asm volatile("fence.acq_rel.gpu;" ::: "memory"); }
__device__ __forceinline__ void fence_proxy_async() { asm volatile("fence.proxy.async;" ::: "memory"); }
__device__ __forceinline__ void bar_sync(int id, int n) { asm volatile("bar.sync %0, %1;" ::"r"(id), "r"(n) : "memory"); }
__device__ __forceinline__ void bar_arrive(int id, int n) { asm volatile("bar.arrive %0, %1;" ::"r"(id), "r"(n) : "memory"); }
__device__ __forceinline__ void wg_fence() { asm volatile("wgmma.fence.sync.aligned;" ::: "memory"); }
__device__ __forceinline__ void wg_commit() { asm volatile("wgmma.commit_group.sync.aligned;" ::: "memory"); }
template <int N> __device__ __forceinline__ void wg_wait() { asm volatile("wgmma.wait_group.sync.aligned %0;" ::"n"(N) : "memory"); }
template <int N> __device__ __forceinline__ void reg_fence(float (&d)[N]) {
#pragma unroll
  for (int i = 0; i < N; i++) asm volatile("" : "+f"(d[i])::"memory");
}
__device__ __forceinline__ uint32_t pack_bf16(float lo, float hi) {
  uint32_t r; asm("cvt.rn.bf16x2.f32 %0, %1, %2;" : "=r"(r) : "f"(hi), "f"(lo)); return r;
}
__device__ __forceinline__ float ex2(float x) { float y; asm("ex2.approx.ftz.f32 %0, %1;" : "=f"(y) : "f"(x)); return y; }
__device__ __forceinline__ uint64_t make_desc(uint32_t addr, uint32_t lbo, uint32_t sbo) {
  return (uint64_t)((addr & 0x3FFFF) >> 4) | ((uint64_t)(lbo >> 4) << 16) | ((uint64_t)(sbo >> 4) << 32) | (1ull << 62);
}

__device__ __forceinline__ void wgmma_ss_n192_tb(float (&d)[96], uint64_t da, uint64_t db, int sd) {
  asm volatile("{\n.reg .pred p;\nsetp.ne.b32 p, %98, 0;\n"
    "wgmma.mma_async.sync.aligned.m64n192k16.f32.bf16.bf16 "
    "{"
    "%0, %1, %2, %3, %4, %5, %6, %7, %8, %9, %10, %11, %12, %13, %14, %15, "
    "%16, %17, %18, %19, %20, %21, %22, %23, %24, %25, %26, %27, %28, %29, %30, %31, "
    "%32, %33, %34, %35, %36, %37, %38, %39, %40, %41, %42, %43, %44, %45, %46, %47, "
    "%48, %49, %50, %51, %52, %53, %54, %55, %56, %57, %58, %59, %60, %61, %62, %63, "
    "%64, %65, %66, %67, %68, %69, %70, %71, %72, %73, %74, %75, %76, %77, %78, %79, "
    "%80, %81, %82, %83, %84, %85, %86, %87, %88, %89, %90, %91, %92, %93, %94, %95"
    "}, %96, %97, p, 1, 1, 0, 1;\n}\n"
    : "+f"(d[0]), "+f"(d[1]), "+f"(d[2]), "+f"(d[3]), "+f"(d[4]), "+f"(d[5]), "+f"(d[6]), "+f"(d[7]),
      "+f"(d[8]), "+f"(d[9]), "+f"(d[10]), "+f"(d[11]), "+f"(d[12]), "+f"(d[13]), "+f"(d[14]), "+f"(d[15]),
      "+f"(d[16]), "+f"(d[17]), "+f"(d[18]), "+f"(d[19]), "+f"(d[20]), "+f"(d[21]), "+f"(d[22]), "+f"(d[23]),
      "+f"(d[24]), "+f"(d[25]), "+f"(d[26]), "+f"(d[27]), "+f"(d[28]), "+f"(d[29]), "+f"(d[30]), "+f"(d[31]),
      "+f"(d[32]), "+f"(d[33]), "+f"(d[34]), "+f"(d[35]), "+f"(d[36]), "+f"(d[37]), "+f"(d[38]), "+f"(d[39]),
      "+f"(d[40]), "+f"(d[41]), "+f"(d[42]), "+f"(d[43]), "+f"(d[44]), "+f"(d[45]), "+f"(d[46]), "+f"(d[47]),
      "+f"(d[48]), "+f"(d[49]), "+f"(d[50]), "+f"(d[51]), "+f"(d[52]), "+f"(d[53]), "+f"(d[54]), "+f"(d[55]),
      "+f"(d[56]), "+f"(d[57]), "+f"(d[58]), "+f"(d[59]), "+f"(d[60]), "+f"(d[61]), "+f"(d[62]), "+f"(d[63]),
      "+f"(d[64]), "+f"(d[65]), "+f"(d[66]), "+f"(d[67]), "+f"(d[68]), "+f"(d[69]), "+f"(d[70]), "+f"(d[71]),
      "+f"(d[72]), "+f"(d[73]), "+f"(d[74]), "+f"(d[75]), "+f"(d[76]), "+f"(d[77]), "+f"(d[78]), "+f"(d[79]),
      "+f"(d[80]), "+f"(d[81]), "+f"(d[82]), "+f"(d[83]), "+f"(d[84]), "+f"(d[85]), "+f"(d[86]), "+f"(d[87]),
      "+f"(d[88]), "+f"(d[89]), "+f"(d[90]), "+f"(d[91]), "+f"(d[92]), "+f"(d[93]), "+f"(d[94]), "+f"(d[95])
    : "l"(da), "l"(db), "r"(sd));
}
__device__ __forceinline__ void wgmma_rs_n192_tb(float (&d)[96], uint32_t a0, uint32_t a1, uint32_t a2, uint32_t a3, uint64_t db, int sd) {
  asm volatile("{\n.reg .pred p;\nsetp.ne.b32 p, %101, 0;\n"
    "wgmma.mma_async.sync.aligned.m64n192k16.f32.bf16.bf16 "
    "{"
    "%0, %1, %2, %3, %4, %5, %6, %7, %8, %9, %10, %11, %12, %13, %14, %15, "
    "%16, %17, %18, %19, %20, %21, %22, %23, %24, %25, %26, %27, %28, %29, %30, %31, "
    "%32, %33, %34, %35, %36, %37, %38, %39, %40, %41, %42, %43, %44, %45, %46, %47, "
    "%48, %49, %50, %51, %52, %53, %54, %55, %56, %57, %58, %59, %60, %61, %62, %63, "
    "%64, %65, %66, %67, %68, %69, %70, %71, %72, %73, %74, %75, %76, %77, %78, %79, "
    "%80, %81, %82, %83, %84, %85, %86, %87, %88, %89, %90, %91, %92, %93, %94, %95"
    "}, {%96, %97, %98, %99}, %100, p, 1, 1, 1;\n}\n"
    : "+f"(d[0]), "+f"(d[1]), "+f"(d[2]), "+f"(d[3]), "+f"(d[4]), "+f"(d[5]), "+f"(d[6]), "+f"(d[7]),
      "+f"(d[8]), "+f"(d[9]), "+f"(d[10]), "+f"(d[11]), "+f"(d[12]), "+f"(d[13]), "+f"(d[14]), "+f"(d[15]),
      "+f"(d[16]), "+f"(d[17]), "+f"(d[18]), "+f"(d[19]), "+f"(d[20]), "+f"(d[21]), "+f"(d[22]), "+f"(d[23]),
      "+f"(d[24]), "+f"(d[25]), "+f"(d[26]), "+f"(d[27]), "+f"(d[28]), "+f"(d[29]), "+f"(d[30]), "+f"(d[31]),
      "+f"(d[32]), "+f"(d[33]), "+f"(d[34]), "+f"(d[35]), "+f"(d[36]), "+f"(d[37]), "+f"(d[38]), "+f"(d[39]),
      "+f"(d[40]), "+f"(d[41]), "+f"(d[42]), "+f"(d[43]), "+f"(d[44]), "+f"(d[45]), "+f"(d[46]), "+f"(d[47]),
      "+f"(d[48]), "+f"(d[49]), "+f"(d[50]), "+f"(d[51]), "+f"(d[52]), "+f"(d[53]), "+f"(d[54]), "+f"(d[55]),
      "+f"(d[56]), "+f"(d[57]), "+f"(d[58]), "+f"(d[59]), "+f"(d[60]), "+f"(d[61]), "+f"(d[62]), "+f"(d[63]),
      "+f"(d[64]), "+f"(d[65]), "+f"(d[66]), "+f"(d[67]), "+f"(d[68]), "+f"(d[69]), "+f"(d[70]), "+f"(d[71]),
      "+f"(d[72]), "+f"(d[73]), "+f"(d[74]), "+f"(d[75]), "+f"(d[76]), "+f"(d[77]), "+f"(d[78]), "+f"(d[79]),
      "+f"(d[80]), "+f"(d[81]), "+f"(d[82]), "+f"(d[83]), "+f"(d[84]), "+f"(d[85]), "+f"(d[86]), "+f"(d[87]),
      "+f"(d[88]), "+f"(d[89]), "+f"(d[90]), "+f"(d[91]), "+f"(d[92]), "+f"(d[93]), "+f"(d[94]), "+f"(d[95])
    : "r"(a0), "r"(a1), "r"(a2), "r"(a3), "l"(db), "r"(sd));
}
__device__ __forceinline__ void wgmma_rs_n128_tb(float (&d)[64], uint32_t a0, uint32_t a1, uint32_t a2, uint32_t a3, uint64_t db, int sd) {
  asm volatile("{\n.reg .pred p;\nsetp.ne.b32 p, %69, 0;\n"
    "wgmma.mma_async.sync.aligned.m64n128k16.f32.bf16.bf16 "
    "{"
    "%0, %1, %2, %3, %4, %5, %6, %7, %8, %9, %10, %11, %12, %13, %14, %15, "
    "%16, %17, %18, %19, %20, %21, %22, %23, %24, %25, %26, %27, %28, %29, %30, %31, "
    "%32, %33, %34, %35, %36, %37, %38, %39, %40, %41, %42, %43, %44, %45, %46, %47, "
    "%48, %49, %50, %51, %52, %53, %54, %55, %56, %57, %58, %59, %60, %61, %62, %63"
    "}, {%64, %65, %66, %67}, %68, p, 1, 1, 1;\n}\n"
    : "+f"(d[0]), "+f"(d[1]), "+f"(d[2]), "+f"(d[3]), "+f"(d[4]), "+f"(d[5]), "+f"(d[6]), "+f"(d[7]),
      "+f"(d[8]), "+f"(d[9]), "+f"(d[10]), "+f"(d[11]), "+f"(d[12]), "+f"(d[13]), "+f"(d[14]), "+f"(d[15]),
      "+f"(d[16]), "+f"(d[17]), "+f"(d[18]), "+f"(d[19]), "+f"(d[20]), "+f"(d[21]), "+f"(d[22]), "+f"(d[23]),
      "+f"(d[24]), "+f"(d[25]), "+f"(d[26]), "+f"(d[27]), "+f"(d[28]), "+f"(d[29]), "+f"(d[30]), "+f"(d[31]),
      "+f"(d[32]), "+f"(d[33]), "+f"(d[34]), "+f"(d[35]), "+f"(d[36]), "+f"(d[37]), "+f"(d[38]), "+f"(d[39]),
      "+f"(d[40]), "+f"(d[41]), "+f"(d[42]), "+f"(d[43]), "+f"(d[44]), "+f"(d[45]), "+f"(d[46]), "+f"(d[47]),
      "+f"(d[48]), "+f"(d[49]), "+f"(d[50]), "+f"(d[51]), "+f"(d[52]), "+f"(d[53]), "+f"(d[54]), "+f"(d[55]),
      "+f"(d[56]), "+f"(d[57]), "+f"(d[58]), "+f"(d[59]), "+f"(d[60]), "+f"(d[61]), "+f"(d[62]), "+f"(d[63])
    : "r"(a0), "r"(a1), "r"(a2), "r"(a3), "l"(db), "r"(sd));
}
__device__ __forceinline__ void wgmma_rs_n128(float (&d)[64], uint32_t a0, uint32_t a1, uint32_t a2, uint32_t a3, uint64_t db, int sd) {
  asm volatile("{\n.reg .pred p;\nsetp.ne.b32 p, %69, 0;\n"
    "wgmma.mma_async.sync.aligned.m64n128k16.f32.bf16.bf16 "
    "{"
    "%0, %1, %2, %3, %4, %5, %6, %7, %8, %9, %10, %11, %12, %13, %14, %15, "
    "%16, %17, %18, %19, %20, %21, %22, %23, %24, %25, %26, %27, %28, %29, %30, %31, "
    "%32, %33, %34, %35, %36, %37, %38, %39, %40, %41, %42, %43, %44, %45, %46, %47, "
    "%48, %49, %50, %51, %52, %53, %54, %55, %56, %57, %58, %59, %60, %61, %62, %63"
    "}, {%64, %65, %66, %67}, %68, p, 1, 1, 0;\n}\n"
    : "+f"(d[0]), "+f"(d[1]), "+f"(d[2]), "+f"(d[3]), "+f"(d[4]), "+f"(d[5]), "+f"(d[6]), "+f"(d[7]),
      "+f"(d[8]), "+f"(d[9]), "+f"(d[10]), "+f"(d[11]), "+f"(d[12]), "+f"(d[13]), "+f"(d[14]), "+f"(d[15]),
      "+f"(d[16]), "+f"(d[17]), "+f"(d[18]), "+f"(d[19]), "+f"(d[20]), "+f"(d[21]), "+f"(d[22]), "+f"(d[23]),
      "+f"(d[24]), "+f"(d[25]), "+f"(d[26]), "+f"(d[27]), "+f"(d[28]), "+f"(d[29]), "+f"(d[30]), "+f"(d[31]),
      "+f"(d[32]), "+f"(d[33]), "+f"(d[34]), "+f"(d[35]), "+f"(d[36]), "+f"(d[37]), "+f"(d[38]), "+f"(d[39]),
      "+f"(d[40]), "+f"(d[41]), "+f"(d[42]), "+f"(d[43]), "+f"(d[44]), "+f"(d[45]), "+f"(d[46]), "+f"(d[47]),
      "+f"(d[48]), "+f"(d[49]), "+f"(d[50]), "+f"(d[51]), "+f"(d[52]), "+f"(d[53]), "+f"(d[54]), "+f"(d[55]),
      "+f"(d[56]), "+f"(d[57]), "+f"(d[58]), "+f"(d[59]), "+f"(d[60]), "+f"(d[61]), "+f"(d[62]), "+f"(d[63])
    : "r"(a0), "r"(a1), "r"(a2), "r"(a3), "l"(db), "r"(sd));
}

#define SCHED 1

__global__ void __launch_bounds__(kThreads, 1) fused_kernel(const __grid_constant__ Maps maps, const __grid_constant__ Params p) {
  extern __shared__ uint8_t smem_raw[];
  __shared__ uint64_t bars[32];
  __shared__ int s_item[2];
  __shared__ int s_slot[32];
  const uint32_t smem = (smem_u32(smem_raw) + 1023u) & ~1023u;
  const uint32_t b_full = smem_u32(&bars[0]), b_empty = smem_u32(&bars[4]);
  const uint32_t b_ofull = smem_u32(&bars[8]), b_oempty = smem_u32(&bars[12]);
  const uint32_t b_ifull = smem_u32(&bars[16]), b_iempty = smem_u32(&bars[18]);
  const uint32_t b_odone = smem_u32(&bars[20]), b_sfree = smem_u32(&bars[21]), b_fin = smem_u32(&bars[22]);
  const int warp = threadIdx.x >> 5, lane = threadIdx.x & 31;
  const uint32_t tstart = clk32();
  if (threadIdx.x == 0) {
    for (int i = 0; i < kStages; i++) {
      mbar_init(b_full + 8 * i, 1); mbar_init(b_empty + 8 * i, 8);
      mbar_init(b_ofull + 8 * i, 1); mbar_init(b_oempty + 8 * i, 8);
    }
    for (int i = 0; i < 2; i++) { mbar_init(b_ifull + 8 * i, 1); mbar_init(b_iempty + 8 * i, 9); }
    mbar_init(b_odone, 8); mbar_init(b_sfree, 1); mbar_init(b_fin, 2);
    asm volatile("fence.mbarrier_init.release.cluster;" ::: "memory");
  }
  __syncthreads();
  const int cta = blockIdx.x, nctas = gridDim.x;
  const bool is_op = ((cta & 3) == 3) && ((cta >> 2) < kNumOp);
  const int opi = cta >> 2;

  if (warp >= 8) {
    asm volatile("setmaxnreg.dec.sync.aligned.u32 24;");
    if (warp == 8) {
      int cnt = 0;
      if (lane == 0) {
        uint64_t pol_ef;
        asm volatile("createpolicy.fractional.L2::evict_first.b64 %0, 1.0;" : "=l"(pol_ef));
        int it = cta, n = 0;
        {
          const int n_att = nctas - kNumOp;
          const int atti = cta - min((cta + 1) >> 2, kNumOp);
          const int rank = is_op ? 0 : (atti * 37) % n_att;
          const int d = (int)((long long)p.qstag * rank / n_att);
          while ((int)(clk32() - tstart) < d) {}
        }
        while (true) {
          mbar_wait(b_iempty + 8 * (n & 1), ((n >> 1) & 1) ^ 1);
          s_item[n & 1] = it;
          mbar_arrive(b_ifull + 8 * (n & 1));
          if (it >= kItems) break;
          const int h = it >> 4, br = (it >> 3) & 1, b = it & 7;
          for (int j = 0; j < 10; j++) {
            const int st = cnt & 3;
            mbar_wait(b_empty + 8 * st, ((cnt >> 2) & 1) ^ 1);
            const uint32_t fb = b_full + 8 * st, d = smem + st * kAttSlot;
            mbar_expect(fb, 16384 + 24576);
            tma2n(d, &maps.x[br], fb, j * 64, b * 128);
            tma3n(d + 16384, &maps.wq[br], fb, 0, j * 64, h * 3);
            cnt++;
          }
          int nit = kItems;
          for (int j = 0; j < 16; j++) {
            if (j == p.late) {
              if (!is_op) nit = nctas + atomicAdd(&g_sync.next, 1);
              if (p.wpf) {
                l2_prefetch((const uint8_t*)p.wo[br] + ((size_t)h * 192 + b * 24) * 1280, 24 * 1280);
                if (nit < kItems) for (int jj = nit & 7; jj < 10; jj += 8) l2_prefetch_t3(&maps.wq[(nit >> 3) & 1], 0, jj * 64, (nit >> 4) * 3);
              }
            }
            const int st = cnt & 3;
            mbar_wait(b_empty + 8 * st, ((cnt >> 2) & 1) ^ 1);
            if (j >= p.win) { const int q = cnt - p.win; mbar_wait(b_full + 8 * (q & 3), (q >> 2) & 1); }
            const uint32_t fb = b_full + 8 * st;
            mbar_expect(fb, kAttSlot);
            tma3(smem + st * kAttSlot, (j & 1) ? &maps.v[br] : &maps.k[br], fb, 0, (b * 32 + h) * 1024 + (j >> 1) * 128, 0, pol_ef);
            cnt++;
          }
          n++; it = nit;
        }
        if (is_op) for (int j = 0; j < kStages; j++) { mbar_wait(b_empty + 8 * (cnt & 3), ((cnt >> 2) & 1) ^ 1); cnt++; }
      }
      __syncwarp();
      if (is_op) {
        const int g = opi >> 1, half = opi & 1, br = g >> 3;
        uint32_t pending = 0xFFFFFFFFu;
        int oc = 0;
        for (int k = 0; k < 32; k++) {
          int e; uint32_t ready; int spin = 0;
          while (true) {
            e = ld_acquire(&g_sync.flag[g * 32 + lane]);
            ready = __ballot_sync(0xFFFFFFFFu, e != 0) & pending;
            if (ready) break;
            if (++spin > (1 << 22)) __trap();
            __nanosleep(40);
          }
          const int h = __ffs(ready) - 1;
          const int slot = __shfl_sync(0xFFFFFFFFu, e, h) - 1;
          pending &= ~(1u << h);
          __syncwarp();
          if (lane == 0) {
            fence_proxy_async();
            s_slot[k] = slot;
            for (int j = 0; j < 3; j++) {
              const int st = oc & 3;
              mbar_wait(b_oempty + 8 * st, ((oc >> 2) & 1) ^ 1);
              const uint32_t fb = b_ofull + 8 * st, d = smem + st * kOpSlot;
              mbar_expect(fb, kOpSlot);
              bulk_g2s(d, (const uint8_t*)g_obuf + (size_t)slot * 49152 + j * 16384, 16384, fb);
              tma3n(d + 16384, &maps.wo[br], fb, 0, h * 192 + j * 64, half * 5);
              oc++;
            }
          }
          __syncwarp();
        }
      }
      if (lane == 0) mbar_arrive(b_fin);
    } else if (warp == 9) {
      if (lane == 0) {
        int n = 0;
        while (true) {
          mbar_wait(b_ifull + 8 * (n & 1), (n >> 1) & 1);
          const int it = s_item[n & 1];
          mbar_arrive(b_iempty + 8 * (n & 1));
          if (it >= kItems) break;
          int spin = 0;
          while (ld_acquire(&g_sync.consumed[cta]) < 2 * n) { if (++spin > (1 << 22)) __trap(); __nanosleep(100); }
          mbar_arrive(b_sfree);
          mbar_wait(b_odone, n & 1);
          fence_gpu();
          fence_proxy_async();
          st_relaxed(&g_sync.flag[(it & 15) * 32 + (it >> 4)], cta + 1);
          n++;
        }
        mbar_wait(b_fin, 0);
        fence_gpu();
      }
      __syncwarp();
      int last = 0;
      if (lane == 0) last = (atomicAdd(&g_sync.done, 1) == nctas - 1);
      last = __shfl_sync(0xFFFFFFFFu, last, 0);
      if (last) {
        fence_gpu();
        int* s = (int*)&g_sync;
        for (int i = lane; i < (int)(sizeof(Sync) / 4); i += 32) s[i] = 0;
      }
    } else if (warp == 10) {
      if (lane == 0) {
        const int h = cta >> 4, br = (cta >> 3) & 1, b = cta & 7;
        tmap_prefetch(&maps.k[br]); tmap_prefetch(&maps.v[br]);
        uint64_t pol_ef;
        asm volatile("createpolicy.fractional.L2::evict_first.b64 %0, 1.0;" : "=l"(pol_ef));
        const uint8_t* kb = (const uint8_t*)p.k[br] + (size_t)(b * 32 + h) * 1024 * 384;
        const uint8_t* vb = (const uint8_t*)p.v[br] + (size_t)(b * 32 + h) * 1024 * 384;
        const int np = p.pf0 >> 3;
        for (int i = 0; i < np; i++) {
          const int tile = i / 6, off = (i % 6) * 8192;
          l2_prefetch_pol(((tile & 1) ? vb : kb) + (tile >> 1) * 49152 + off, 8192, pol_ef);
          const uint32_t t = tstart + (i + 1) * p.pftau;
          while ((int)(clk32() - t) < 0) {}
        }
      }
    }
  } else {
    asm volatile("setmaxnreg.inc.sync.aligned.u32 240;");
    const int wg = warp >> 2;
    const float kScale = 0.07216878364870322f * 1.4426950408889634f;
    int cnt = 0, n = 0;
    if (SCHED != 0 && wg == 1) bar_arrive(1, 256);
    while (true) {
      mbar_wait(b_ifull + 8 * (n & 1), (n >> 1) & 1);
      const int it = s_item[n & 1];
      __syncwarp();
      if (lane == 0) mbar_arrive(b_iempty + 8 * (n & 1));
      if (it >= kItems) break;
      float o[96];
#pragma unroll 1
      for (int j = 0; j < 10; j++) {
        const int st = cnt & 3;
        mbar_wait(b_full + 8 * st, (cnt >> 2) & 1);
        const uint32_t base = smem + st * kAttSlot;
        const uint64_t da = make_desc(base + wg * 8192, 16, 1024), db = make_desc(base + 16384, 8192, 1024);
        wg_fence();
#pragma unroll
        for (int k = 0; k < 4; k++) wgmma_ss_n192_tb(o, da + k * 2, db + k * 128, (j | k) != 0);
        wg_commit();
        if (j > 0) { wg_wait<1>(); if (lane == 0) mbar_arrive(b_empty + 8 * ((cnt - 1) & 3)); }
        cnt++;
      }
      wg_wait<0>();
      reg_fence(o);
      if (lane == 0) mbar_arrive(b_empty + 8 * ((cnt - 1) & 3));
      uint32_t q[48];
#pragma unroll
      for (int i = 0; i < 48; i++) q[i] = pack_bf16(o[2 * i], o[2 * i + 1]);
      float m0 = -INFINITY, m1 = -INFINITY, l0 = 0.f, l1 = 0.f;
#pragma unroll 1
      for (int j = 0; j < 8; j++) {
        float s[64];
        {
          const int st = cnt & 3;
          mbar_wait(b_full + 8 * st, (cnt >> 2) & 1);
          const uint64_t db = make_desc(smem + st * kAttSlot, 16, 1024);
          if (SCHED == 2 || (SCHED == 1 && j == 0)) bar_sync(1 + wg, 256);
          wg_fence();
#pragma unroll
          for (int k = 0; k < 12; k++)
            wgmma_rs_n128(s, q[4 * k], q[4 * k + 1], q[4 * k + 2], q[4 * k + 3], db + (k >> 2) * 1024 + (k & 3) * 2, k != 0);
          wg_commit();
          if (SCHED != 0) bar_arrive(2 - wg, 256);
          wg_wait<0>();
          reg_fence(s);
          if (lane == 0) mbar_arrive(b_empty + 8 * st);
          cnt++;
        }
        float x0 = fmaxf(s[0], s[1]), x1 = fmaxf(s[2], s[3]);
#pragma unroll
        for (int i = 1; i < 16; i++) {
          x0 = fmaxf(x0, fmaxf(s[4 * i], s[4 * i + 1]));
          x1 = fmaxf(x1, fmaxf(s[4 * i + 2], s[4 * i + 3]));
        }
        x0 = fmaxf(x0, __shfl_xor_sync(0xFFFFFFFFu, x0, 1)); x1 = fmaxf(x1, __shfl_xor_sync(0xFFFFFFFFu, x1, 1));
        x0 = fmaxf(x0, __shfl_xor_sync(0xFFFFFFFFu, x0, 2)); x1 = fmaxf(x1, __shfl_xor_sync(0xFFFFFFFFu, x1, 2));
        const float n0 = fmaxf(m0, x0), n1 = fmaxf(m1, x1);
        const float r0 = ex2((m0 - n0) * kScale), r1 = ex2((m1 - n1) * kScale);
        m0 = n0; m1 = n1;
        const float c0 = -n0 * kScale, c1 = -n1 * kScale;
        uint32_t pr[32];
        float a0 = 0.f, a1 = 0.f;
#pragma unroll
        for (int i = 0; i < 16; i++) {
          const float e0 = ex2(fmaf(s[4 * i], kScale, c0)), e1 = ex2(fmaf(s[4 * i + 1], kScale, c0));
          const float e2 = ex2(fmaf(s[4 * i + 2], kScale, c1)), e3 = ex2(fmaf(s[4 * i + 3], kScale, c1));
          a0 += e0 + e1; a1 += e2 + e3;
          pr[2 * i] = pack_bf16(e0, e1); pr[2 * i + 1] = pack_bf16(e2, e3);
        }
        l0 = fmaf(l0, r0, a0); l1 = fmaf(l1, r1, a1);
#pragma unroll
        for (int i = 0; i < 24; i++) { o[4 * i] *= r0; o[4 * i + 1] *= r0; o[4 * i + 2] *= r1; o[4 * i + 3] *= r1; }
        {
          const int st = cnt & 3;
          mbar_wait(b_full + 8 * st, (cnt >> 2) & 1);
          const uint64_t db = make_desc(smem + st * kAttSlot, 16384, 1024);
          if (SCHED != 0) bar_sync(1 + wg, 256);
          reg_fence(o);
          wg_fence();
#pragma unroll
          for (int k = 0; k < 8; k++)
            wgmma_rs_n192_tb(o, pr[4 * k], pr[4 * k + 1], pr[4 * k + 2], pr[4 * k + 3], db + k * 128, (j | k) != 0);
          wg_commit();
          if (SCHED == 2 || (SCHED == 1 && j == 7)) bar_arrive(2 - wg, 256);
          wg_wait<0>();
          reg_fence(o);
          if (lane == 0) mbar_arrive(b_empty + 8 * st);
          cnt++;
        }
      }
      l0 += __shfl_xor_sync(0xFFFFFFFFu, l0, 1); l1 += __shfl_xor_sync(0xFFFFFFFFu, l1, 1);
      l0 += __shfl_xor_sync(0xFFFFFFFFu, l0, 2); l1 += __shfl_xor_sync(0xFFFFFFFFu, l1, 2);
      const float i0 = 1.f / l0, i1 = 1.f / l1;
      mbar_wait(b_sfree, n & 1);
      uint4* dst = g_obuf + (size_t)cta * 3072 + threadIdx.x;
#pragma unroll
      for (int k = 0; k < 12; k++) {
        uint4 v;
        v.x = pack_bf16(o[8 * k] * i0, o[8 * k + 1] * i0);     v.y = pack_bf16(o[8 * k + 2] * i1, o[8 * k + 3] * i1);
        v.z = pack_bf16(o[8 * k + 4] * i0, o[8 * k + 5] * i0); v.w = pack_bf16(o[8 * k + 6] * i1, o[8 * k + 7] * i1);
        dst[k * 256] = v;
      }
      __syncwarp();
      if (lane == 0) mbar_arrive(b_odone);
      n++;
    }
    if (is_op) {
      float c0[96], c1[64];
      uint32_t a[2][16];
#pragma unroll 1
      for (int s2 = 0; s2 < 48; s2++) {
#pragma unroll
        for (int u = 0; u < 2; u++) {
          const int s = 2 * s2 + u, st = s & 3;
          mbar_wait(b_ofull + 8 * st, (s >> 2) & 1);
          const uint32_t base = smem + st * kOpSlot;
#pragma unroll
          for (int k = 0; k < 4; k++)
            asm volatile("ld.shared.v4.u32 {%0, %1, %2, %3}, [%4];"
                         : "=r"(a[u][4 * k]), "=r"(a[u][4 * k + 1]), "=r"(a[u][4 * k + 2]), "=r"(a[u][4 * k + 3])
                         : "r"(base + k * 4096 + threadIdx.x * 16) : "memory");
          if (threadIdx.x == 0 && (s % 3) == 2) {
            red_add_relaxed(&g_sync.consumed[s_slot[s / 3]], 1);
            if (s == 95) mbar_arrive(b_fin);
          }
          const uint64_t db = make_desc(base + 16384, 8192, 1024);
          wg_fence();
#pragma unroll
          for (int k = 0; k < 4; k++) {
            wgmma_rs_n192_tb(c0, a[u][4 * k], a[u][4 * k + 1], a[u][4 * k + 2], a[u][4 * k + 3], db + k * 128, (s | k) != 0);
            wgmma_rs_n128_tb(c1, a[u][4 * k], a[u][4 * k + 1], a[u][4 * k + 2], a[u][4 * k + 3], db + 1536 + k * 128, (s | k) != 0);
          }
          wg_commit();
          if (s > 0) { wg_wait<1>(); if (lane == 0) mbar_arrive(b_oempty + 8 * ((s - 1) & 3)); }
        }
      }
      wg_wait<0>();
      reg_fence(c0); reg_fence(c1);
      const int g = opi >> 1, half = opi & 1;
      const int row = (g & 7) * 128 + wg * 64 + (warp & 3) * 16 + (lane >> 2);
      __nv_bfloat16* orow = p.out + (size_t)row * 1280 + (g >> 3) * 640 + half * 320;
      const int qd = lane & 3;
#pragma unroll
      for (int t = 0; t < 10; t++) {
#pragma unroll
        for (int r = 0; r < 2; r++) {
          uint32_t w[4];
#pragma unroll
          for (int i = 0; i < 4; i++) {
            const int gidx = 4 * t + i;
            if (gidx < 24) w[i] = pack_bf16(c0[(gidx < 24 ? gidx : 0) * 4 + 2 * r], c0[(gidx < 24 ? gidx : 0) * 4 + 2 * r + 1]);
            else           w[i] = pack_bf16(c1[(gidx >= 24 ? gidx - 24 : 0) * 4 + 2 * r], c1[(gidx >= 24 ? gidx - 24 : 0) * 4 + 2 * r + 1]);
          }
          uint32_t u0 = (qd & 1) ? w[0] : w[1], u1 = (qd & 1) ? w[2] : w[3];
          u0 = __shfl_xor_sync(0xFFFFFFFFu, u0, 1); u1 = __shfl_xor_sync(0xFFFFFFFFu, u1, 1);
          if (qd & 1) { w[0] = u0; w[2] = u1; } else { w[1] = u0; w[3] = u1; }
          u0 = (qd & 2) ? w[0] : w[2]; u1 = (qd & 2) ? w[1] : w[3];
          u0 = __shfl_xor_sync(0xFFFFFFFFu, u0, 2); u1 = __shfl_xor_sync(0xFFFFFFFFu, u1, 2);
          if (qd & 2) { w[0] = u0; w[1] = u1; } else { w[2] = u0; w[3] = u1; }
          *(uint4*)(orow + (size_t)r * 8 * 1280 + (4 * t + qd) * 8) = make_uint4(w[0], w[1], w[2], w[3]);
        }
      }
    } else {
      if (threadIdx.x == 0) mbar_arrive(b_fin);
    }
  }
}

typedef CUresult (*EncodeFn)(CUtensorMap*, CUtensorMapDataType, cuuint32_t, void*, const cuuint64_t*, const cuuint64_t*,
                             const cuuint32_t*, const cuuint32_t*, CUtensorMapInterleave, CUtensorMapSwizzle,
                             CUtensorMapL2promotion, CUtensorMapFloatOOBfill);

void encode(EncodeFn fn, CUtensorMap* m, int rank, const void* ptr, cuuint64_t d0, cuuint64_t d1, cuuint64_t d2,
            cuuint64_t s1, cuuint64_t s2, cuuint32_t b0, cuuint32_t b1, cuuint32_t b2) {
  cuuint64_t dims[3] = {d0, d1, d2}, strides[2] = {s1, s2};
  cuuint32_t box[3] = {b0, b1, b2}, es[3] = {1, 1, 1};
  fn(m, CU_TENSOR_MAP_DATA_TYPE_BFLOAT16, rank, const_cast<void*>(ptr), dims, strides, box, es, CU_TENSOR_MAP_INTERLEAVE_NONE,
     CU_TENSOR_MAP_SWIZZLE_128B, CU_TENSOR_MAP_L2_PROMOTION_NONE, CU_TENSOR_MAP_FLOAT_OOB_FILL_NONE);
}

}

extern "C" void kernel_launch(void* const* d_in, const int* in_sizes, int n_in, void* d_out, int out_size) {
  static EncodeFn fn = nullptr;
  static int sms = 0;
  if (!fn) {
    void* f = nullptr; cudaDriverEntryPointQueryResult qr;
    cudaGetDriverEntryPoint("cuTensorMapEncodeTiled", &f, cudaEnableDefault, &qr);
    fn = (EncodeFn)f;
    int dev = 0; cudaGetDevice(&dev);
    cudaDeviceGetAttribute(&sms, cudaDevAttrMultiProcessorCount, dev);
    if (sms > kMaxCtas) sms = kMaxCtas;
    cudaFuncSetAttribute(fused_kernel, cudaFuncAttributeMaxDynamicSharedMemorySize, kSmemBytes);
  }
  Maps m; Params p;
  for (int i = 0; i < 2; i++) {
    const void *x = d_in[5 * i], *k = d_in[5 * i + 1], *v = d_in[5 * i + 2], *wq = d_in[5 * i + 3], *wo = d_in[5 * i + 4];
    encode(fn, &m.k[i], 3, k, 64, 262144, 3, 384, 128, 64, 128, 3);
    encode(fn, &m.v[i], 3, v, 64, 262144, 3, 384, 128, 64, 128, 3);
    encode(fn, &m.x[i], 2, x, 640, 1024, 1, 1280, 0, 64, 128, 1);
    encode(fn, &m.wq[i], 3, wq, 64, 640, 96, 12288, 128, 64, 64, 3);
    encode(fn, &m.wo[i], 3, wo, 64, 6144, 10, 1280, 128, 64, 64, 5);
    p.k[i] = (const __nv_bfloat16*)k; p.v[i] = (const __nv_bfloat16*)v; p.wo[i] = (const __nv_bfloat16*)wo;
  }
  p.out = (__nv_bfloat16*)d_out;
  p.qstag = 30000; p.win = 2; p.late = 12; p.pf0 = 96; p.pftau = 700; p.wpf = 1;
  fused_kernel<<<sms, kThreads, kSmemBytes, cudaStreamPerThread>>>(m, p);
}
```

```cpp
#include <cuda_runtime.h>
#include <cuda.h>
#include <cuda_bf16.h>
#include <stdint.h>

namespace {

constexpr int kItems    = 512;
constexpr int kNumOp    = 32;
constexpr int kSlots    = 64;
constexpr int kSplit    = 22;
constexpr int kHelpFrom = 28;
constexpr int kNumHelp  = 48;
constexpr int kWindow   = 4;
constexpr int kStagger  = 30000;
constexpr int kEarly    = kNumOp + 6;
constexpr int kStages   = 4;
constexpr int kAttSlot  = 49152;
constexpr int kOpSlot   = 57344;
constexpr int kTileBytes = kStages * kOpSlot;
constexpr int kSmemBytes = kTileBytes + 512;
constexpr int kThreads  = 384;
static_assert(kItems - kSlots <= 16 * kHelpFrom && (3 * kHelpFrom) % 4 == 0, "");

struct Maps { CUtensorMap k[2], v[2], x[2], wq[2], wo3[2], wo2[2], wo1[2], out; };
constexpr int kMaxCtas = 160;
struct Params {
  const uint8_t* k[2]; const uint8_t* v[2];
  uint8_t first[kMaxCtas];
};

__device__ uint4 g_obuf[kSlots * 3072];
__device__ uint4 g_pbuf[kSplit * 3328];
__device__ uint4 g_cbuf[kNumOp * 6144];
struct Sync {
  int next; int pad[31];
  int flag[kItems];
  int consumed[kSlots];
  int pflag[kSplit];
  int hflag[kNumOp], early[16];
};
__device__ Sync g_syncs[2];
__device__ unsigned long long g_arrivals;

constexpr uint32_t kSmemBase = 1024, kBars = kSmemBase + kTileBytes;
constexpr uint32_t b_full = kBars;
constexpr uint32_t b_empty = kBars + 64, b_ofull = kBars + 96, b_oempty = kBars + 128;
constexpr uint32_t b_ifull = kBars + 160, b_iempty = kBars + 176;
constexpr uint32_t b_odone = kBars + 208, b_last = kBars + 224;
constexpr uint32_t b_sfree = kBars + 240, b_epoch = kBars + 248, b_opgo = kBars + 256;
constexpr uint32_t b_fetch = kBars + 264, b_hdone = kBars + 272, b_hready = kBars + 280;
constexpr uint32_t s_task = kBars + 320, s_mode = kBars + 328, s_par = kBars + 332;

constexpr int kHead = 1, kTail = 2;
constexpr int kNoTask = 3 << 16;
__device__ __forceinline__ int item_at(int t) {
  if (t < 2) return t * 8;
  const int u = t - 2;
  if (u < kItems - 16) return (u & 7) ? u : u + 16;
  return u < kItems - 9 ? u + 1 : u + 2;
}
__device__ __forceinline__ int decode_task(int t) {
  if (t < kItems - kSplit) return item_at(t);
  if (t < kItems) return item_at(t) | ((t - (kItems - kSplit)) << 9) | (kHead << 16);
  if (t < kItems + kSplit) return item_at(t - kSplit) | ((t - kItems) << 9) | (kTail << 16);
  const int v = t - (kItems + kSplit), g = v / 3, r = v - 3 * g;
  return v >= kNumHelp ? kNoTask : (r < 2 ? ((2 * g + r) | (5 << 16)) : ((2 * g) | (6 << 16)));
}
__device__ __forceinline__ int split_index(int task) { return (task >> 9) & 127; }
__device__ __forceinline__ int slot_of(int item) { return item & (kSlots - 1); }

__device__ __forceinline__ void mbar_init(uint32_t b, uint32_t c) { asm volatile("mbarrier.init.shared::cta.b64 [%0], %1;" ::"r"(b), "r"(c)); }
__device__ __forceinline__ void mbar_expect(uint32_t b, uint32_t bytes) { asm volatile("mbarrier.arrive.expect_tx.shared::cta.b64 _, [%0], %1;" ::"r"(b), "r"(bytes) : "memory"); }
__device__ __forceinline__ void mbar_arrive(uint32_t b) { asm volatile("mbarrier.arrive.shared::cta.b64 _, [%0];" ::"r"(b) : "memory"); }
__device__ __forceinline__ void mbar_arrive_warp(uint32_t b) {
  asm volatile("{\n.reg .pred p;\nelect.sync _|p, 0xFFFFFFFF;\n@p mbarrier.arrive.shared::cta.b64 _, [%0];\n}" ::"r"(b) : "memory");
}
__device__ __forceinline__ bool mbar_try(uint32_t b, uint32_t ph) {
  uint32_t ok;
  asm volatile("{\n.reg .pred p;\nmbarrier.try_wait.parity.shared::cta.b64 p, [%1], %2;\nselp.u32 %0, 1, 0, p;\n}" : "=r"(ok) : "r"(b), "r"(ph) : "memory");
  return ok;
}
__device__ __forceinline__ void mbar_wait(uint32_t b, uint32_t ph) {
  if (mbar_try(b, ph)) return;
#pragma unroll 1
  for (int i = 0; i < (1 << 24); i++) if (mbar_try(b, ph)) return;
  __trap();
}
__device__ __forceinline__ int ld_acquire(const int* p) { int v; asm volatile("ld.acquire.gpu.global.s32 %0, [%1];" : "=r"(v) : "l"(p) : "memory"); return v; }
__device__ __forceinline__ void poll(const int* f, int n) {
  int spin = 0;
  while (ld_acquire(f) < n) if (++spin > (1 << 23)) __trap();
}
__device__ __forceinline__ void publish(int* f) {
  asm volatile("fence.acq_rel.gpu;\nst.relaxed.gpu.global.s32 [%0], 1;" ::"l"(f) : "memory");
}
__device__ __forceinline__ void red_add(int* p) { asm volatile("red.relaxed.gpu.global.add.s32 [%0], 1;" ::"l"(p) : "memory"); }
__device__ __forceinline__ uint32_t clk32() { uint32_t c; asm volatile("mov.u32 %0, %%clock;" : "=r"(c)); return c; }
__device__ __forceinline__ uint32_t tid_now() { uint32_t t; asm volatile("mov.u32 %0, %%tid.x;" : "=r"(t)); return t; }
__device__ __forceinline__ int lds32(uint32_t a) { int v; asm volatile("ld.shared.s32 %0, [%1];" : "=r"(v) : "r"(a) : "memory"); return v; }
__device__ __forceinline__ void sts32(uint32_t a, int v) { asm volatile("st.shared.s32 [%0], %1;" ::"r"(a), "r"(v) : "memory"); }
__device__ __forceinline__ uint4 ldg_l2(const uint4* p) {
  uint4 v; asm volatile("ld.relaxed.gpu.global.v4.u32 {%0, %1, %2, %3}, [%4];" : "=r"(v.x), "=r"(v.y), "=r"(v.z), "=r"(v.w) : "l"(p) : "memory"); return v;
}
__device__ __forceinline__ void tma3_stream(uint32_t dst, const CUtensorMap* m, uint32_t bar, int c1) {
  asm volatile("{\n.reg .b64 pol;\ncreatepolicy.fractional.L2::evict_first.b64 pol, 1.0;\n"
               "cp.async.bulk.tensor.3d.shared::cluster.global.mbarrier::complete_tx::bytes.L2::cache_hint [%0], [%1, {%3, %4, %3}], [%2], pol;\n}"
               ::"r"(dst), "l"(m), "r"(bar), "r"(0), "r"(c1) : "memory");
}
__device__ __forceinline__ void tma3(uint32_t dst, const CUtensorMap* m, uint32_t bar, int c1, int c2) {
  asm volatile("cp.async.bulk.tensor.3d.shared::cluster.global.mbarrier::complete_tx::bytes [%0], [%1, {%3, %4, %5}], [%2];"
               ::"r"(dst), "l"(m), "r"(bar), "r"(0), "r"(c1), "r"(c2) : "memory");
}
__device__ __forceinline__ void tma2(uint32_t dst, const CUtensorMap* m, uint32_t bar, int c0, int c1) {
  asm volatile("cp.async.bulk.tensor.2d.shared::cluster.global.mbarrier::complete_tx::bytes [%0], [%1, {%3, %4}], [%2];"
               ::"r"(dst), "l"(m), "r"(bar), "r"(c0), "r"(c1) : "memory");
}
__device__ __forceinline__ void bulk_g2s(uint32_t dst, const void* src, uint32_t bytes, uint32_t bar) {
  asm volatile("cp.async.bulk.shared::cluster.global.mbarrier::complete_tx::bytes [%0], [%1], %2, [%3];"
               ::"r"(dst), "l"(src), "r"(bytes), "r"(bar) : "memory");
}
__device__ __forceinline__ void l2_prefetch_stream(const void* src, uint32_t bytes) {
  asm volatile("{\n.reg .b64 pol;\ncreatepolicy.fractional.L2::evict_first.b64 pol, 1.0;\n"
               "cp.async.bulk.prefetch.L2.global.L2::cache_hint [%0], %1, pol;\n}" ::"l"(src), "r"(bytes) : "memory");
}
__device__ __forceinline__ void tmap_prefetch(const CUtensorMap* m) { asm volatile("prefetch.tensormap [%0];" ::"l"(m) : "memory"); }
__device__ __forceinline__ void bar_sync(int id, int n) { asm volatile("bar.sync %0, %1;" ::"r"(id), "r"(n) : "memory"); }
__device__ __forceinline__ void bar_arrive(int id, int n) { asm volatile("bar.arrive %0, %1;" ::"r"(id), "r"(n) : "memory"); }
__device__ __forceinline__ void wg_fence() { asm volatile("wgmma.fence.sync.aligned;" ::: "memory"); }
__device__ __forceinline__ void wg_commit() { asm volatile("wgmma.commit_group.sync.aligned;" ::: "memory"); }
template <int N> __device__ __forceinline__ void wg_wait() { asm volatile("wgmma.wait_group.sync.aligned %0;" ::"n"(N) : "memory"); }
template <int N> __device__ __forceinline__ void reg_fence(float (&d)[N]) {
#pragma unroll
  for (int i = 0; i < N; i++) asm volatile("" : "+f"(d[i])::"memory");
}
__device__ __forceinline__ uint32_t pack_bf16(float lo, float hi) {
  uint32_t r; asm("cvt.rn.bf16x2.f32 %0, %1, %2;" : "=r"(r) : "f"(hi), "f"(lo)); return r;
}
__device__ __forceinline__ float ex2(float x) { float y; asm("ex2.approx.ftz.f32 %0, %1;" : "=f"(y) : "f"(x)); return y; }
__device__ __forceinline__ uint64_t make_desc(uint32_t addr, uint32_t lbo, uint32_t sbo) {
  return (uint64_t)((addr & 0x3FFFF) >> 4) | ((uint64_t)(lbo >> 4) << 16) | ((uint64_t)(sbo >> 4) << 32) | (1ull << 62);
}
__device__ __forceinline__ Sync* sync_copy() { mbar_wait(b_epoch, 0); return &g_syncs[lds32(s_par)]; }

__device__ __forceinline__ void wgmma_ss_n192_tb(float (&d)[96], uint64_t da, uint64_t db, int sd) {
  asm volatile("{\n.reg .pred p;\nsetp.ne.b32 p, %98, 0;\n"
    "wgmma.mma_async.sync.aligned.m64n192k16.f32.bf16.bf16 "
    "{"
    "%0, %1, %2, %3, %4, %5, %6, %7, %8, %9, %10, %11, %12, %13, %14, %15, "
    "%16, %17, %18, %19, %20, %21, %22, %23, %24, %25, %26, %27, %28, %29, %30, %31, "
    "%32, %33, %34, %35, %36, %37, %38, %39, %40, %41, %42, %43, %44, %45, %46, %47, "
    "%48, %49, %50, %51, %52, %53, %54, %55, %56, %57, %58, %59, %60, %61, %62, %63, "
    "%64, %65, %66, %67, %68, %69, %70, %71, %72, %73, %74, %75, %76, %77, %78, %79, "
    "%80, %81, %82, %83, %84, %85, %86, %87, %88, %89, %90, %91, %92, %93, %94, %95"
    "}, %96, %97, p, 1, 1, 0, 1;\n}\n"
    : "+f"(d[0]), "+f"(d[1]), "+f"(d[2]), "+f"(d[3]), "+f"(d[4]), "+f"(d[5]), "+f"(d[6]), "+f"(d[7]),
      "+f"(d[8]), "+f"(d[9]), "+f"(d[10]), "+f"(d[11]), "+f"(d[12]), "+f"(d[13]), "+f"(d[14]), "+f"(d[15]),
      "+f"(d[16]), "+f"(d[17]), "+f"(d[18]), "+f"(d[19]), "+f"(d[20]), "+f"(d[21]), "+f"(d[22]), "+f"(d[23]),
      "+f"(d[24]), "+f"(d[25]), "+f"(d[26]), "+f"(d[27]), "+f"(d[28]), "+f"(d[29]), "+f"(d[30]), "+f"(d[31]),
      "+f"(d[32]), "+f"(d[33]), "+f"(d[34]), "+f"(d[35]), "+f"(d[36]), "+f"(d[37]), "+f"(d[38]), "+f"(d[39]),
      "+f"(d[40]), "+f"(d[41]), "+f"(d[42]), "+f"(d[43]), "+f"(d[44]), "+f"(d[45]), "+f"(d[46]), "+f"(d[47]),
      "+f"(d[48]), "+f"(d[49]), "+f"(d[50]), "+f"(d[51]), "+f"(d[52]), "+f"(d[53]), "+f"(d[54]), "+f"(d[55]),
      "+f"(d[56]), "+f"(d[57]), "+f"(d[58]), "+f"(d[59]), "+f"(d[60]), "+f"(d[61]), "+f"(d[62]), "+f"(d[63]),
      "+f"(d[64]), "+f"(d[65]), "+f"(d[66]), "+f"(d[67]), "+f"(d[68]), "+f"(d[69]), "+f"(d[70]), "+f"(d[71]),
      "+f"(d[72]), "+f"(d[73]), "+f"(d[74]), "+f"(d[75]), "+f"(d[76]), "+f"(d[77]), "+f"(d[78]), "+f"(d[79]),
      "+f"(d[80]), "+f"(d[81]), "+f"(d[82]), "+f"(d[83]), "+f"(d[84]), "+f"(d[85]), "+f"(d[86]), "+f"(d[87]),
      "+f"(d[88]), "+f"(d[89]), "+f"(d[90]), "+f"(d[91]), "+f"(d[92]), "+f"(d[93]), "+f"(d[94]), "+f"(d[95])
    : "l"(da), "l"(db), "r"(sd));
}
__device__ __forceinline__ void wgmma_rs_n192_tb(float (&d)[96], uint32_t a0, uint32_t a1, uint32_t a2, uint32_t a3, uint64_t db, int sd) {
  asm volatile("{\n.reg .pred p;\nsetp.ne.b32 p, %101, 0;\n"
    "wgmma.mma_async.sync.aligned.m64n192k16.f32.bf16.bf16 "
    "{"
    "%0, %1, %2, %3, %4, %5, %6, %7, %8, %9, %10, %11, %12, %13, %14, %15, "
    "%16, %17, %18, %19, %20, %21, %22, %23, %24, %25, %26, %27, %28, %29, %30, %31, "
    "%32, %33, %34, %35, %36, %37, %38, %39, %40, %41, %42, %43, %44, %45, %46, %47, "
    "%48, %49, %50, %51, %52, %53, %54, %55, %56, %57, %58, %59, %60, %61, %62, %63, "
    "%64, %65, %66, %67, %68, %69, %70, %71, %72, %73, %74, %75, %76, %77, %78, %79, "
    "%80, %81, %82, %83, %84, %85, %86, %87, %88, %89, %90, %91, %92, %93, %94, %95"
    "}, {%96, %97, %98, %99}, %100, p, 1, 1, 1;\n}\n"
    : "+f"(d[0]), "+f"(d[1]), "+f"(d[2]), "+f"(d[3]), "+f"(d[4]), "+f"(d[5]), "+f"(d[6]), "+f"(d[7]),
      "+f"(d[8]), "+f"(d[9]), "+f"(d[10]), "+f"(d[11]), "+f"(d[12]), "+f"(d[13]), "+f"(d[14]), "+f"(d[15]),
      "+f"(d[16]), "+f"(d[17]), "+f"(d[18]), "+f"(d[19]), "+f"(d[20]), "+f"(d[21]), "+f"(d[22]), "+f"(d[23]),
      "+f"(d[24]), "+f"(d[25]), "+f"(d[26]), "+f"(d[27]), "+f"(d[28]), "+f"(d[29]), "+f"(d[30]), "+f"(d[31]),
      "+f"(d[32]), "+f"(d[33]), "+f"(d[34]), "+f"(d[35]), "+f"(d[36]), "+f"(d[37]), "+f"(d[38]), "+f"(d[39]),
      "+f"(d[40]), "+f"(d[41]), "+f"(d[42]), "+f"(d[43]), "+f"(d[44]), "+f"(d[45]), "+f"(d[46]), "+f"(d[47]),
      "+f"(d[48]), "+f"(d[49]), "+f"(d[50]), "+f"(d[51]), "+f"(d[52]), "+f"(d[53]), "+f"(d[54]), "+f"(d[55]),
      "+f"(d[56]), "+f"(d[57]), "+f"(d[58]), "+f"(d[59]), "+f"(d[60]), "+f"(d[61]), "+f"(d[62]), "+f"(d[63]),
      "+f"(d[64]), "+f"(d[65]), "+f"(d[66]), "+f"(d[67]), "+f"(d[68]), "+f"(d[69]), "+f"(d[70]), "+f"(d[71]),
      "+f"(d[72]), "+f"(d[73]), "+f"(d[74]), "+f"(d[75]), "+f"(d[76]), "+f"(d[77]), "+f"(d[78]), "+f"(d[79]),
      "+f"(d[80]), "+f"(d[81]), "+f"(d[82]), "+f"(d[83]), "+f"(d[84]), "+f"(d[85]), "+f"(d[86]), "+f"(d[87]),
      "+f"(d[88]), "+f"(d[89]), "+f"(d[90]), "+f"(d[91]), "+f"(d[92]), "+f"(d[93]), "+f"(d[94]), "+f"(d[95])
    : "r"(a0), "r"(a1), "r"(a2), "r"(a3), "l"(db), "r"(sd));
}
__device__ __forceinline__ void wgmma_rs_n128_tb(float (&d)[64], uint32_t a0, uint32_t a1, uint32_t a2, uint32_t a3, uint64_t db, int sd) {
  asm volatile("{\n.reg .pred p;\nsetp.ne.b32 p, %69, 0;\n"
    "wgmma.mma_async.sync.aligned.m64n128k16.f32.bf16.bf16 "
    "{"
    "%0, %1, %2, %3, %4, %5, %6, %7, %8, %9, %10, %11, %12, %13, %14, %15, "
    "%16, %17, %18, %19, %20, %21, %22, %23, %24, %25, %26, %27, %28, %29, %30, %31, "
    "%32, %33, %34, %35, %36, %37, %38, %39, %40, %41, %42, %43, %44, %45, %46, %47, "
    "%48, %49, %50, %51, %52, %53, %54, %55, %56, %57, %58, %59, %60, %61, %62, %63"
    "}, {%64, %65, %66, %67}, %68, p, 1, 1, 1;\n}\n"
    : "+f"(d[0]), "+f"(d[1]), "+f"(d[2]), "+f"(d[3]), "+f"(d[4]), "+f"(d[5]), "+f"(d[6]), "+f"(d[7]),
      "+f"(d[8]), "+f"(d[9]), "+f"(d[10]), "+f"(d[11]), "+f"(d[12]), "+f"(d[13]), "+f"(d[14]), "+f"(d[15]),
      "+f"(d[16]), "+f"(d[17]), "+f"(d[18]), "+f"(d[19]), "+f"(d[20]), "+f"(d[21]), "+f"(d[22]), "+f"(d[23]),
      "+f"(d[24]), "+f"(d[25]), "+f"(d[26]), "+f"(d[27]), "+f"(d[28]), "+f"(d[29]), "+f"(d[30]), "+f"(d[31]),
      "+f"(d[32]), "+f"(d[33]), "+f"(d[34]), "+f"(d[35]), "+f"(d[36]), "+f"(d[37]), "+f"(d[38]), "+f"(d[39]),
      "+f"(d[40]), "+f"(d[41]), "+f"(d[42]), "+f"(d[43]), "+f"(d[44]), "+f"(d[45]), "+f"(d[46]), "+f"(d[47]),
      "+f"(d[48]), "+f"(d[49]), "+f"(d[50]), "+f"(d[51]), "+f"(d[52]), "+f"(d[53]), "+f"(d[54]), "+f"(d[55]),
      "+f"(d[56]), "+f"(d[57]), "+f"(d[58]), "+f"(d[59]), "+f"(d[60]), "+f"(d[61]), "+f"(d[62]), "+f"(d[63])
    : "r"(a0), "r"(a1), "r"(a2), "r"(a3), "l"(db), "r"(sd));
}
__device__ __forceinline__ void wgmma_rs_n128_tb96(float (&d)[96], uint32_t a0, uint32_t a1, uint32_t a2, uint32_t a3, uint64_t db, int sd) {
  asm volatile("{\n.reg .pred p;\nsetp.ne.b32 p, %69, 0;\n"
    "wgmma.mma_async.sync.aligned.m64n128k16.f32.bf16.bf16 "
    "{"
    "%0, %1, %2, %3, %4, %5, %6, %7, %8, %9, %10, %11, %12, %13, %14, %15, "
    "%16, %17, %18, %19, %20, %21, %22, %23, %24, %25, %26, %27, %28, %29, %30, %31, "
    "%32, %33, %34, %35, %36, %37, %38, %39, %40, %41, %42, %43, %44, %45, %46, %47, "
    "%48, %49, %50, %51, %52, %53, %54, %55, %56, %57, %58, %59, %60, %61, %62, %63"
    "}, {%64, %65, %66, %67}, %68, p, 1, 1, 1;\n}\n"
    : "+f"(d[0]), "+f"(d[1]), "+f"(d[2]), "+f"(d[3]), "+f"(d[4]), "+f"(d[5]), "+f"(d[6]), "+f"(d[7]),
      "+f"(d[8]), "+f"(d[9]), "+f"(d[10]), "+f"(d[11]), "+f"(d[12]), "+f"(d[13]), "+f"(d[14]), "+f"(d[15]),
      "+f"(d[16]), "+f"(d[17]), "+f"(d[18]), "+f"(d[19]), "+f"(d[20]), "+f"(d[21]), "+f"(d[22]), "+f"(d[23]),
      "+f"(d[24]), "+f"(d[25]), "+f"(d[26]), "+f"(d[27]), "+f"(d[28]), "+f"(d[29]), "+f"(d[30]), "+f"(d[31]),
      "+f"(d[32]), "+f"(d[33]), "+f"(d[34]), "+f"(d[35]), "+f"(d[36]), "+f"(d[37]), "+f"(d[38]), "+f"(d[39]),
      "+f"(d[40]), "+f"(d[41]), "+f"(d[42]), "+f"(d[43]), "+f"(d[44]), "+f"(d[45]), "+f"(d[46]), "+f"(d[47]),
      "+f"(d[48]), "+f"(d[49]), "+f"(d[50]), "+f"(d[51]), "+f"(d[52]), "+f"(d[53]), "+f"(d[54]), "+f"(d[55]),
      "+f"(d[56]), "+f"(d[57]), "+f"(d[58]), "+f"(d[59]), "+f"(d[60]), "+f"(d[61]), "+f"(d[62]), "+f"(d[63])
    : "r"(a0), "r"(a1), "r"(a2), "r"(a3), "l"(db), "r"(sd));
}
__device__ __forceinline__ void wgmma_rs_n64(float (&d)[32], uint32_t a0, uint32_t a1, uint32_t a2, uint32_t a3, uint64_t db, int sd) {
  asm volatile("{\n.reg .pred p;\nsetp.ne.b32 p, %37, 0;\n"
    "wgmma.mma_async.sync.aligned.m64n64k16.f32.bf16.bf16 "
    "{"
    "%0, %1, %2, %3, %4, %5, %6, %7, %8, %9, %10, %11, %12, %13, %14, %15, "
    "%16, %17, %18, %19, %20, %21, %22, %23, %24, %25, %26, %27, %28, %29, %30, %31"
    "}, {%32, %33, %34, %35}, %36, p, 1, 1, 0;\n}\n"
    : "+f"(d[0]), "+f"(d[1]), "+f"(d[2]), "+f"(d[3]), "+f"(d[4]), "+f"(d[5]), "+f"(d[6]), "+f"(d[7]),
      "+f"(d[8]), "+f"(d[9]), "+f"(d[10]), "+f"(d[11]), "+f"(d[12]), "+f"(d[13]), "+f"(d[14]), "+f"(d[15]),
      "+f"(d[16]), "+f"(d[17]), "+f"(d[18]), "+f"(d[19]), "+f"(d[20]), "+f"(d[21]), "+f"(d[22]), "+f"(d[23]),
      "+f"(d[24]), "+f"(d[25]), "+f"(d[26]), "+f"(d[27]), "+f"(d[28]), "+f"(d[29]), "+f"(d[30]), "+f"(d[31])
    : "r"(a0), "r"(a1), "r"(a2), "r"(a3), "l"(db), "r"(sd));
}

__device__ __forceinline__ void exp_sum(float (&s)[32], float c, float c0, float c1, float& l0, float& l1) {
  float a0 = 0.f, a1 = 0.f;
#pragma unroll
  for (int i = 0; i < 8; i++) {
    s[4 * i]     = ex2(fmaf(s[4 * i], c, c0));     s[4 * i + 1] = ex2(fmaf(s[4 * i + 1], c, c0));
    s[4 * i + 2] = ex2(fmaf(s[4 * i + 2], c, c1)); s[4 * i + 3] = ex2(fmaf(s[4 * i + 3], c, c1));
    if (i & 1) { a0 += s[4 * i] + s[4 * i + 1]; a1 += s[4 * i + 2] + s[4 * i + 3]; }
    else       { l0 += s[4 * i] + s[4 * i + 1]; l1 += s[4 * i + 2] + s[4 * i + 3]; }
  }
  l0 += a0; l1 += a1;
}

__device__ __forceinline__ void qp_stage(const Maps& maps, int task, int j, int st) {
  const uint32_t fb = b_full + 16 * st, d = kSmemBase + st * kAttSlot;
  const int br = (task >> 3) & 1;
  mbar_expect(fb, 16384);
  tma2(d, &maps.x[br], fb, j * 64, (task & 7) * 128);
  mbar_expect(fb + 8, 24576);
  tma3(d + 16384, &maps.wq[br], fb + 8, j * 64, ((task >> 4) & 31) * 3);
}

__global__ void __launch_bounds__(kThreads, 1) fused_kernel(const __grid_constant__ Maps maps, const __grid_constant__ Params p) {
  extern __shared__ __align__(1024) uint8_t smem_raw[];
  const uint32_t tstart = clk32();
  uint32_t smid, nsmid;
  asm volatile("mov.u32 %0, %%smid;\nmov.u32 %1, %%nsmid;" : "=r"(smid), "=r"(nsmid));
  const int pos0 = p.first[nsmid == gridDim.x ? smid : blockIdx.x], item0 = item_at(pos0);
  if (threadIdx.x == 32) {
    if (pos0 >= (int)gridDim.x - 60 && pos0 >= kEarly) {
      const size_t off = (size_t)((item0 & 7) * 32 + (item0 >> 4)) * 1024 * 384;
      const uint8_t* kb = p.k[(item0 >> 3) & 1] + off;
      const uint8_t* vb = p.v[(item0 >> 3) & 1] + off;
      uint32_t t = tstart + 600;
#pragma unroll 1
      for (int i = 0; i < 20; i++) {
        while ((int)(clk32() - t) < 0) {}
        l2_prefetch_stream(((i & 1) ? vb : kb) + (i >> 1) * 8192, 8192);
        t += 400;
      }
    }
  }
  if (threadIdx.x == 0) {
    if ((uint32_t)__cvta_generic_to_shared(smem_raw) != kSmemBase) __trap();
    for (int i = 0; i < kStages; i++) {
      mbar_init(b_full + 16 * i, 1); mbar_init(b_full + 16 * i + 8, 1); mbar_init(b_empty + 8 * i, 8);
      mbar_init(b_ofull + 8 * i, 2); mbar_init(b_oempty + 8 * i, 8);
    }
    for (int i = 0; i < 2; i++) {
      mbar_init(b_ifull + 8 * i, 1); mbar_init(b_iempty + 8 * i, 10);
      mbar_init(b_odone + 8 * i, 4); mbar_init(b_last + 8 * i, 1);
    }
    mbar_init(b_sfree, 1); mbar_init(b_epoch, 1); mbar_init(b_opgo, 1);
    mbar_init(b_fetch, 1); mbar_init(b_hdone, 8); mbar_init(b_hready, 1);
    asm volatile("fence.mbarrier_init.release.cluster;\nfence.proxy.async.shared::cta;" ::: "memory");
    if (pos0 < kEarly) {
#pragma unroll 1
      for (int j = 0; j < kStages; j++) qp_stage(maps, item0, j, j);
    }
  }
  __syncthreads();
  const int warp = __shfl_sync(0xFFFFFFFFu, threadIdx.x >> 5, 0);

  if (warp >= 8) {
    asm volatile("setmaxnreg.dec.sync.aligned.u32 24;");
    const bool lane0 = (threadIdx.x & 31) == 0;
    if (warp == 8) {
      if (lane0) {
        int cnt = pos0 < kEarly ? kStages : 0, task;
#pragma unroll 1
        for (int n = 0;; n++) {
          mbar_wait(b_ifull + 8 * (n & 1), (n >> 1) & 1);
          task = lds32(s_task + 4 * (n & 1));
          mbar_arrive(b_iempty + 8 * (n & 1));
          if (task >= kNoTask) break;
          const int h = (task >> 4) & 31, br = (task >> 3) & 1, b = task & 7, kind = task >> 16;
#pragma unroll 1
          for (int j = n == 0 ? cnt : 0; j < 10; j++) {
            mbar_wait(b_empty + 8 * (cnt & 3), ((cnt >> 2) & 1) ^ 1);
            qp_stage(maps, task, j, cnt & 3);
            cnt++;
          }
          const int j1 = kind ? 8 : 16, row0 = (b * 32 + h) * 1024 + (kind == kTail ? 512 : 0);
#pragma unroll 1
          for (int j = 0; j < j1; j++) {
            const int st = cnt & 3;
            mbar_wait(b_empty + 8 * st, ((cnt >> 2) & 1) ^ 1);
            if (j == j1 - 2) mbar_arrive(b_fetch);
#pragma unroll 1
            for (int u = 0; u < 2; u++) {
              if (2 * j + u >= kWindow) { const int q = 2 * cnt + u - kWindow; mbar_wait(b_full + 8 * (q & 7), (q >> 3) & 1); }
              const uint32_t fb = b_full + 16 * st + 8 * u;
              mbar_expect(fb, 24576);
              tma3_stream(kSmemBase + st * kAttSlot + u * 24576, (j & 1) ? &maps.v[br] : &maps.k[br], fb,
                          row0 + (j >> 1) * 128 + u * 64);
            }
            cnt++;
          }
        }
#pragma unroll 1
        for (int j = 0; j < kStages; j++) { mbar_wait(b_empty + 8 * (cnt & 3), ((cnt >> 2) & 1) ^ 1); cnt++; }
        sts32(s_mode, task);
        mbar_arrive(b_opgo);
        if (task != kNoTask) {
          const int kind = task >> 16;
          const int s0 = kind >= 5 ? 3 * kHelpFrom : 0, br = (task >> 4) & 1, c0 = (task & 1) * 5;
#pragma unroll 1
          for (int s = s0; s < 96; s++) {
            const int st = s & 3;
            mbar_wait(b_oempty + 8 * st, (((s - s0) >> 2) & 1) ^ 1);
            const uint32_t fb = b_ofull + 8 * st, d = kSmemBase + st * kOpSlot + 16384;
            if (s >= 93) mbar_arrive(fb);
            if (s < 3 * kHelpFrom) {
              mbar_expect(fb, 40960);
              tma3(d, &maps.wo3[br], fb, s * 64, c0);
              tma3(d + 24576, &maps.wo2[br], fb, s * 64, c0 + 3);
            } else {
              mbar_expect(fb, 16384);
              if (kind == 6) {
                tma3(d, &maps.wo1[br], fb, s * 64, 2);
                tma3(d + 8192, &maps.wo1[br], fb, s * 64, 7);
              } else {
                tma3(d, &maps.wo2[br], fb, s * 64, kind == 5 ? c0 + 3 : c0);
              }
            }
          }
        }
      }
    } else if (warp == 9) {
      int par = 0;
      if (lane0) {
        par = (int)((atomicAdd(&g_arrivals, 1ull) / gridDim.x) & 1);
        sts32(s_par, par);
        mbar_arrive(b_epoch);
      }
      if (blockIdx.x == 0) {
        int* z = (int*)&g_syncs[__shfl_sync(0xFFFFFFFFu, par, 0) ^ 1];
#pragma unroll 1
        for (int i = threadIdx.x & 31; i < (int)(sizeof(Sync) / 4); i += 32) z[i] = 0;
      }
      if (lane0) {
        Sync& sy = g_syncs[par];
        int task;
#pragma unroll 1
        for (int n = 0;; n++) {
          mbar_wait(b_ifull + 8 * (n & 1), (n >> 1) & 1);
          task = lds32(s_task + 4 * (n & 1));
          mbar_arrive(b_iempty + 8 * (n & 1));
          if (task >= kNoTask) break;
          const int item = task & 511, kind = task >> 16;
          if (kind == kHead) {
            mbar_arrive(b_sfree);
            mbar_wait(b_odone, n & 1); mbar_wait(b_odone + 8, n & 1);
            publish(&sy.pflag[split_index(task)]);
          } else {
            int spin = 0;
            while (ld_acquire(&sy.consumed[slot_of(item)]) < 2 * (item / kSlots)) { if (++spin > (1 << 22)) __trap(); __nanosleep(100); }
            if (kind == kTail) poll(&sy.pflag[split_index(task)], 1);
            mbar_arrive(b_sfree);
            mbar_wait(b_odone, n & 1);
            if (item >= kItems - 16) publish(&sy.early[item & 15]);
            mbar_wait(b_odone + 8, n & 1);
            publish(&sy.flag[(item & 15) * 32 + (item >> 4)]);
          }
        }
        if ((task >> 16) == 4) {
          mbar_wait(b_hdone, 0);
          publish(&sy.hflag[task & 31]);
        }
      }
    } else if (warp == 10) {
      if (lane0) {
        mbar_wait(b_opgo, 0);
        const int mode = lds32(s_mode);
        if (mode != kNoTask) {
          Sync& sy = *sync_copy();
          tmap_prefetch(&maps.out);
          const int h0 = (mode >> 16) >= 5 ? kHelpFrom : 0, g = (mode >> 1) & 15;
#pragma unroll 1
          for (int h = h0; h < 31; h++) {
            poll(&sy.flag[g * 32 + h], 1);
            asm volatile("fence.proxy.async;" ::: "memory");
            const uint8_t* src = (const uint8_t*)g_obuf + (size_t)slot_of(h * 16 + g) * 49152;
#pragma unroll 1
            for (int j = 0; j < 3; j++) {
              const int s = h * 3 + j, st = s & 3;
              mbar_wait(b_oempty + 8 * st, (((s - 3 * h0) >> 2) & 1) ^ 1);
              const uint32_t fb = b_ofull + 8 * st;
              mbar_expect(fb, 16384);
              bulk_g2s(kSmemBase + st * kOpSlot, src + j * 16384, 16384, fb);
            }
          }
          poll(&sy.early[g], 1);
          mbar_arrive(b_last);
          poll(&sy.flag[g * 32 + 31], 1);
          mbar_arrive(b_last + 8);
        }
      }
    } else if (lane0) {
      int task = item0;
      tmap_prefetch(&maps.k[(task >> 3) & 1]); tmap_prefetch(&maps.v[(task >> 3) & 1]);
      if (pos0 >= kEarly) {
        const int d = (kStagger * (pos0 - kNumOp)) / ((int)gridDim.x - kNumOp);
        while ((int)(clk32() - tstart) < d) {}
      }
#pragma unroll 1
      for (int n = 0;; n++) {
        mbar_wait(b_iempty + 8 * (n & 1), ((n >> 1) & 1) ^ 1);
        sts32(s_task + 4 * (n & 1), task);
        mbar_arrive(b_ifull + 8 * (n & 1));
        if (task >= kNoTask) break;
        mbar_wait(b_fetch, n & 1);
        task = pos0 < kNumOp ? (pos0 | (4 << 16)) : decode_task(gridDim.x + atomicAdd(&sync_copy()->next, 1));
      }
      if ((task >> 16) >= 5) {
        Sync& sy = *sync_copy();
        poll(&sy.hflag[task & 31], 1);
        if ((task >> 16) == 6) poll(&sy.hflag[(task & 31) + 1], 1);
        mbar_arrive(b_hready);
      }
    }
  } else {
    asm volatile("setmaxnreg.inc.sync.aligned.u32 240;");
    const int wg = warp >> 2;
    const float kScale = 0.07216878364870322f * 1.4426950408889634f;
#define FULL_WAIT(c, u) mbar_wait(b_full + 16 * ((c) & 3) + 8 * (u), ((c) >> 2) & 1)
#define RELEASE(c)      mbar_arrive_warp(b_empty + 8 * ((c) & 3))
#define SLOT(c)         (kSmemBase + ((c) & 3) * kAttSlot)
#define TASK(n)         __shfl_sync(0xFFFFFFFFu, lds32(s_task + 4 * ((n) & 1)), 0)
    int cnt = 0, mode;
    if (wg == 1) bar_arrive(1, 256);
#pragma unroll 1
    for (int n = 0;; n++) {
      mbar_wait(b_ifull + 8 * (n & 1), (n >> 1) & 1);
      int nkv;
      float o[96];
      uint32_t q[48];
      {
        const int task = TASK(n);
        if (task >= kNoTask) { mode = task; break; }
        nkv = (task >> 16) ? 4 : 8;
      }
#pragma unroll 1
      for (int j = 0; j < 10; j++) {
        FULL_WAIT(cnt, 0); FULL_WAIT(cnt, 1);
        const uint64_t da = make_desc(SLOT(cnt) + wg * 8192, 16, 1024), db = make_desc(SLOT(cnt) + 16384, 8192, 1024);
        wg_fence();
#pragma unroll
        for (int k = 0; k < 4; k++) wgmma_ss_n192_tb(o, da + k * 2, db + k * 128, (j | k) != 0);
        wg_commit();
        if (j > 0) { wg_wait<1>(); RELEASE(cnt - 1); }
        cnt++;
      }
      wg_wait<0>();
      RELEASE(cnt - 1);
      reg_fence(o);
#pragma unroll
      for (int i = 0; i < 48; i++) q[i] = pack_bf16(o[2 * i], o[2 * i + 1]);
      float m0 = -INFINITY, m1 = -INFINITY, l0 = 0.f, l1 = 0.f;
      uint32_t pr[32];
#pragma unroll 1
      for (int j = 0; j < nkv; j++) {
        float sa[32], sb[32];
        const uint64_t dk = make_desc(SLOT(cnt), 16, 1024);
        bar_sync(1 + wg, 256);
        reg_fence(o);
        if (j > 0) {
          const uint64_t dv = make_desc(SLOT(cnt - 1), 8192, 1024);
          wg_fence();
#pragma unroll
          for (int k = 0; k < 8; k++)
            wgmma_rs_n192_tb(o, pr[4 * k], pr[4 * k + 1], pr[4 * k + 2], pr[4 * k + 3], dv + (k >> 2) * 1536 + (k & 3) * 128, ((j - 1) | k) != 0);
          wg_commit();
        }
        FULL_WAIT(cnt, 0);
        wg_fence();
#pragma unroll
        for (int k = 0; k < 12; k++)
          wgmma_rs_n64(sa, q[4 * k], q[4 * k + 1], q[4 * k + 2], q[4 * k + 3], dk + (k >> 2) * 512 + (k & 3) * 2, k != 0);
        wg_commit();
        wg_wait<1>();
        if (j > 0) RELEASE(cnt - 1);
        FULL_WAIT(cnt, 1);
        wg_fence();
#pragma unroll
        for (int k = 0; k < 12; k++)
          wgmma_rs_n64(sb, q[4 * k], q[4 * k + 1], q[4 * k + 2], q[4 * k + 3], dk + 1536 + (k >> 2) * 512 + (k & 3) * 2, k != 0);
        wg_commit();
        bar_arrive(2 - wg, 256);
        wg_wait<0>();
        RELEASE(cnt);
        reg_fence(sa); reg_fence(sb); reg_fence(o);
        float x0 = fmaxf(sa[0], sa[1]), x1 = fmaxf(sa[2], sa[3]), y0 = fmaxf(sb[0], sb[1]), y1 = fmaxf(sb[2], sb[3]);
#pragma unroll
        for (int i = 1; i < 8; i++) {
          x0 = fmaxf(x0, fmaxf(sa[4 * i], sa[4 * i + 1])); x1 = fmaxf(x1, fmaxf(sa[4 * i + 2], sa[4 * i + 3]));
          y0 = fmaxf(y0, fmaxf(sb[4 * i], sb[4 * i + 1])); y1 = fmaxf(y1, fmaxf(sb[4 * i + 2], sb[4 * i + 3]));
        }
        x0 = fmaxf(x0, y0); x1 = fmaxf(x1, y1);
        x0 = fmaxf(x0, __shfl_xor_sync(0xFFFFFFFFu, x0, 1)); x1 = fmaxf(x1, __shfl_xor_sync(0xFFFFFFFFu, x1, 1));
        x0 = fmaxf(x0, __shfl_xor_sync(0xFFFFFFFFu, x0, 2)); x1 = fmaxf(x1, __shfl_xor_sync(0xFFFFFFFFu, x1, 2));
        x0 = fmaxf(x0, m0); x1 = fmaxf(x1, m1);
        const float r0 = ex2((m0 - x0) * kScale), r1 = ex2((m1 - x1) * kScale);
        m0 = x0; m1 = x1;
        l0 *= r0; l1 *= r1;
        exp_sum(sa, kScale, -m0 * kScale, -m1 * kScale, l0, l1);
        exp_sum(sb, kScale, -m0 * kScale, -m1 * kScale, l0, l1);
#pragma unroll
        for (int i = 0; i < 16; i++) { pr[i] = pack_bf16(sa[2 * i], sa[2 * i + 1]); pr[16 + i] = pack_bf16(sb[2 * i], sb[2 * i + 1]); }
#pragma unroll
        for (int i = 0; i < 24; i++) { o[4 * i] *= r0; o[4 * i + 1] *= r0; o[4 * i + 2] *= r1; o[4 * i + 3] *= r1; }
        FULL_WAIT(cnt + 1, 0); FULL_WAIT(cnt + 1, 1);
        cnt += 2;
      }
      {
        const uint64_t dv = make_desc(SLOT(cnt - 1), 8192, 1024);
        bar_sync(1 + wg, 256);
        reg_fence(o);
        wg_fence();
#pragma unroll
        for (int k = 0; k < 8; k++)
          wgmma_rs_n192_tb(o, pr[4 * k], pr[4 * k + 1], pr[4 * k + 2], pr[4 * k + 3], dv + (k >> 2) * 1536 + (k & 3) * 128, 1);
        wg_commit();
        bar_arrive(2 - wg, 256);
      }
      l0 += __shfl_xor_sync(0xFFFFFFFFu, l0, 1); l1 += __shfl_xor_sync(0xFFFFFFFFu, l1, 1);
      l0 += __shfl_xor_sync(0xFFFFFFFFu, l0, 2); l1 += __shfl_xor_sync(0xFFFFFFFFu, l1, 2);
      const int task = TASK(n), kind = task >> 16;
      mbar_arrive_warp(b_iempty + 8 * (n & 1));
      uint4* part = g_pbuf + split_index(task) * 3328 + tid_now();
      uint4* dst = kind == kHead ? part : g_obuf + (size_t)slot_of(task & 511) * 3072 + tid_now();
      mbar_wait(b_sfree, n & 1);
      float w0, w1, u0, u1;
      if (kind == kTail) {
        const uint4 st = ldg_l2(part + 3072);
#pragma unroll
        for (int k = 0; k < 12; k++) {
          const uint4 v = ldg_l2(part + k * 256);
          q[4 * k] = v.x; q[4 * k + 1] = v.y; q[4 * k + 2] = v.z; q[4 * k + 3] = v.w;
        }
        const float a0 = __uint_as_float(st.x), a1 = __uint_as_float(st.y);
        const float x0 = fmaxf(m0, a0), x1 = fmaxf(m1, a1);
        w0 = ex2((m0 - x0) * kScale); w1 = ex2((m1 - x1) * kScale);
        u0 = __uint_as_float(st.z) * ex2((a0 - x0) * kScale); u1 = __uint_as_float(st.w) * ex2((a1 - x1) * kScale);
        l0 = fmaf(l0, w0, u0); l1 = fmaf(l1, w1, u1);
      } else {
        if (kind == kHead) part[3072] = make_uint4(__float_as_uint(m0), __float_as_uint(m1), __float_as_uint(l0), __float_as_uint(l1));
        w0 = w1 = u0 = u1 = 0.f;
      }
      wg_wait<0>();
      RELEASE(cnt - 1);
      reg_fence(o);
      if (kind == kTail) {
#pragma unroll
        for (int i = 0; i < 48; i++) {
          const float w = (i & 1) ? w1 : w0, u = (i & 1) ? u1 : u0;
          o[2 * i]     = fmaf(o[2 * i], w, __uint_as_float(q[i] << 16) * u);
          o[2 * i + 1] = fmaf(o[2 * i + 1], w, __uint_as_float(q[i] & 0xFFFF0000u) * u);
        }
      }
      const float i0 = 1.f / l0, i1 = 1.f / l1;
#pragma unroll
      for (int k = 0; k < 12; k++) {
        uint4 v;
        v.x = pack_bf16(o[8 * k] * i0, o[8 * k + 1] * i0);     v.y = pack_bf16(o[8 * k + 2] * i1, o[8 * k + 3] * i1);
        v.z = pack_bf16(o[8 * k + 4] * i0, o[8 * k + 5] * i0); v.w = pack_bf16(o[8 * k + 6] * i1, o[8 * k + 7] * i1);
        dst[k * 256] = v;
      }
      __syncwarp();
      mbar_arrive_warp(b_odone + 8 * wg);
    }

    if (mode != kNoTask) {
      const uint32_t tid = tid_now();
      const int g = (mode >> 1) & 15;
      uint32_t a[3][16];
#define OP_DESC(s) make_desc(kSmemBase + ((s) & 3) * kOpSlot + 16384, 8192, 1024)
#define OP_MMA(f, c, off, sd) f(c, a[u][4 * k], a[u][4 * k + 1], a[u][4 * k + 2], a[u][4 * k + 3], db + (off) + k * 128, sd);
#define OP_HEADS(hb, he, s0, BODY)                                                                                 \
      _Pragma("unroll 1") for (int h = hb; h < he; h++) {                                                           \
        _Pragma("unroll") for (int u = 0; u < 3; u++) {                                                             \
          const int s = 3 * h + u;                                                                                  \
          mbar_wait(b_ofull + 8 * (s & 3), ((s - (s0)) >> 2) & 1);                                                  \
          _Pragma("unroll") for (int k = 0; k < 4; k++)                                                             \
            asm volatile("ld.shared.v4.u32 {%0, %1, %2, %3}, [%4];"                                                 \
                         : "=r"(a[u][4 * k]), "=r"(a[u][4 * k + 1]), "=r"(a[u][4 * k + 2]), "=r"(a[u][4 * k + 3])   \
                         : "r"(kSmemBase + (s & 3) * kOpSlot + k * 4096 + tid * 16) : "memory");                    \
          if (u == 2 && tid == 0 && h < kHelpFrom) red_add(&sync_copy()->consumed[slot_of(h * 16 + g)]);            \
          const uint64_t db = OP_DESC(s);                                                                           \
          wg_fence();                                                                                               \
          _Pragma("unroll") for (int k = 0; k < 4; k++) { BODY }                                                    \
          wg_commit();                                                                                              \
          if (s > (s0)) { wg_wait<1>(); mbar_arrive_warp(b_oempty + 8 * ((s - 1) & 3)); }                           \
        }                                                                                                           \
      }
#define OP_LAST_LD(k0, k1)                                                                                         \
      _Pragma("unroll") for (int k = k0; k < k1; k++) {                                                             \
        const uint4 v = ldg_l2(g_obuf + (size_t)slot_of(kItems - 16 + g) * 3072 + tid + k * 256);                   \
        a[k >> 2][4 * (k & 3)] = v.x; a[k >> 2][4 * (k & 3) + 1] = v.y;                                             \
        a[k >> 2][4 * (k & 3) + 2] = v.z; a[k >> 2][4 * (k & 3) + 3] = v.w;                                         \
      }
#define OP_LAST(s0, BODY)                                                                                          \
      mbar_wait(b_last + 8 * wg, 0);                                                                                \
      OP_LAST_LD(0, 8)                                                                                              \
      wg_wait<0>();                                                                                                 \
      OP_LAST_LD(8, 12)                                                                                             \
      _Pragma("unroll") for (int u = 0; u < 3; u++) mbar_wait(b_ofull + 8 * ((93 + u) & 3), ((93 + u - (s0)) >> 2) & 1); \
      bar_sync(1 + wg, 256);                                                                                        \
      _Pragma("unroll") for (int u = 0; u < 3; u++) {                                                               \
        wg_fence();                                                                                                 \
        _Pragma("unroll") for (int k = 0; k < 4; k++) { const uint64_t db = OP_DESC(93 + u); BODY }                 \
      }                                                                                                             \
      wg_commit();                                                                                                  \
      bar_arrive(2 - wg, 256);                                                                                      \
      wg_wait<0>();
#define OP_OUT(c, col0, col1)                                                                                      \
      _Pragma("unroll") for (int k = 0; k < 8; k++)                                                                 \
        asm volatile("stmatrix.sync.aligned.m8n8.x4.shared.b16 [%0], {%1, %2, %3, %4};"                             \
                     ::"r"(kSmemBase + (1 + (k >> 2)) * kOpSlot + 32768 + ((tid >> 5) * 16 + (tid & 15)) * 128 +    \
                           ((((k & 3) * 2 + ((tid >> 4) & 1)) ^ (tid & 7)) << 4)),                                  \
                     "r"(pack_bf16(c[8 * k], c[8 * k + 1])), "r"(pack_bf16(c[8 * k + 2], c[8 * k + 3])),            \
                     "r"(pack_bf16(c[8 * k + 4], c[8 * k + 5])), "r"(pack_bf16(c[8 * k + 6], c[8 * k + 7])) : "memory"); \
      asm volatile("fence.proxy.async.shared::cta;" ::: "memory");                                                  \
      bar_sync(3 + wg, 128);                                                                                        \
      if ((tid & 127) == 0) {                                                                                       \
        _Pragma("unroll") for (int k = 0; k < 2; k++)                                                               \
          asm volatile("cp.async.bulk.tensor.2d.global.shared::cta.bulk_group [%0, {%2, %3}], [%1];" ::"l"(&maps.out), \
                       "r"(kSmemBase + (1 + k) * kOpSlot + 32768 + wg * 8192),                                      \
                       "r"((g >> 3) * 640 + (mode & 1) * 320 + (k ? (col1) : (col0))), "r"((g & 7) * 128 + wg * 64) : "memory"); \
        asm volatile("cp.async.bulk.commit_group;" ::: "memory");                                                   \
        asm volatile("cp.async.bulk.wait_group.read 0;" ::: "memory");                                              \
      }
      uint4* hand = g_cbuf + (mode & 31) * 6144 + tid;
      if ((mode >> 16) == 4) {
        float c0[96];
        {
          float c1[64];
          OP_HEADS(0, kHelpFrom, 0, OP_MMA(wgmma_rs_n192_tb, c0, 0, (s | k) != 0) OP_MMA(wgmma_rs_n128_tb, c1, 1536, (s | k) != 0))
          wg_wait<0>();
          reg_fence(c1); reg_fence(c0);
#pragma unroll
          for (int i = 0; i < 16; i++)
            hand[i * 256] = make_uint4(__float_as_uint(c1[4 * i]), __float_as_uint(c1[4 * i + 1]), __float_as_uint(c1[4 * i + 2]), __float_as_uint(c1[4 * i + 3]));
#pragma unroll
          for (int i = 16; i < 24; i++)
            hand[i * 256] = make_uint4(__float_as_uint(c0[4 * i]), __float_as_uint(c0[4 * i + 1]), __float_as_uint(c0[4 * i + 2]), __float_as_uint(c0[4 * i + 3]));
          __syncwarp();
          mbar_arrive_warp(b_hdone);
        }
        OP_HEADS(kHelpFrom, 31, 0, OP_MMA(wgmma_rs_n128_tb96, c0, 0, 1))
        OP_LAST(0, OP_MMA(wgmma_rs_n128_tb96, c0, 0, 1))
#pragma unroll
        for (int i = 0; i < 64; i++) asm volatile("" : "+f"(c0[i])::"memory");
        OP_OUT(c0, 0, 64)
      } else {
        const bool mid = (mode >> 16) == 6;
        float c1[64];
        OP_HEADS(kHelpFrom, 30, 3 * kHelpFrom, OP_MMA(wgmma_rs_n128_tb, c1, 0, ((s - 3 * kHelpFrom) | k) != 0))
        mbar_wait(b_hready, 0);
        uint4 pc[16];
#pragma unroll
        for (int i = 0; i < 16; i++) pc[i] = ldg_l2(hand + (mid ? (i < 8 ? 16 + i : 32 + i) : i) * 256);
        OP_HEADS(30, 31, 3 * kHelpFrom, OP_MMA(wgmma_rs_n128_tb, c1, 0, 1))
        OP_LAST(3 * kHelpFrom, OP_MMA(wgmma_rs_n128_tb, c1, 0, 1))
        reg_fence(c1);
#pragma unroll
        for (int i = 0; i < 16; i++) {
          c1[4 * i] += __uint_as_float(pc[i].x); c1[4 * i + 1] += __uint_as_float(pc[i].y);
          c1[4 * i + 2] += __uint_as_float(pc[i].z); c1[4 * i + 3] += __uint_as_float(pc[i].w);
        }
        OP_OUT(c1, mid ? 128 : 192, mid ? 448 : 256)
      }
    }
  }
}

typedef CUresult (*EncodeFn)(CUtensorMap*, CUtensorMapDataType, cuuint32_t, void*, const cuuint64_t*, const cuuint64_t*,
                             const cuuint32_t*, const cuuint32_t*, CUtensorMapInterleave, CUtensorMapSwizzle,
                             CUtensorMapL2promotion, CUtensorMapFloatOOBfill);

void encode(EncodeFn fn, CUtensorMap* m, int rank, const void* ptr, cuuint64_t d0, cuuint64_t d1, cuuint64_t d2,
            cuuint64_t s1, cuuint64_t s2, cuuint32_t b0, cuuint32_t b1, cuuint32_t b2) {
  cuuint64_t dims[3] = {d0, d1, d2}, strides[2] = {s1, s2};
  cuuint32_t box[3] = {b0, b1, b2}, es[3] = {1, 1, 1};
  fn(m, CU_TENSOR_MAP_DATA_TYPE_BFLOAT16, rank, const_cast<void*>(ptr), dims, strides, box, es, CU_TENSOR_MAP_INTERLEAVE_NONE,
     CU_TENSOR_MAP_SWIZZLE_128B, CU_TENSOR_MAP_L2_PROMOTION_NONE, CU_TENSOR_MAP_FLOAT_OOB_FILL_NONE);
}

}

extern "C" void kernel_launch(void* const* d_in, const int* in_sizes, int n_in, void* d_out, int out_size) {
  static EncodeFn fn = nullptr;
  static int sms = 0;
  if (!fn) {
    void* f = nullptr; cudaDriverEntryPointQueryResult qr;
    cudaGetDriverEntryPoint("cuTensorMapEncodeTiled", &f, cudaEnableDefault, &qr);
    fn = (EncodeFn)f;
    int dev = 0; cudaGetDevice(&dev);
    cudaDeviceGetAttribute(&sms, cudaDevAttrMultiProcessorCount, dev);
    if (sms > kMaxCtas) sms = kMaxCtas;
    cudaFuncSetAttribute(fused_kernel, cudaFuncAttributeMaxDynamicSharedMemorySize, kSmemBytes);
  }
  Maps m; Params p;
  for (int i = 0; i < 2; i++) {
    const void *x = d_in[5 * i], *k = d_in[5 * i + 1], *v = d_in[5 * i + 2], *wq = d_in[5 * i + 3], *wo = d_in[5 * i + 4];
    encode(fn, &m.k[i], 3, k, 64, 262144, 3, 384, 128, 64, 64, 3);
    encode(fn, &m.v[i], 3, v, 64, 262144, 3, 384, 128, 64, 64, 3);
    encode(fn, &m.x[i], 2, x, 640, 1024, 1, 1280, 0, 64, 128, 1);
    encode(fn, &m.wq[i], 3, wq, 64, 640, 96, 12288, 128, 64, 64, 3);
    encode(fn, &m.wo3[i], 3, wo, 64, 6144, 10, 1280, 128, 64, 64, 3);
    encode(fn, &m.wo2[i], 3, wo, 64, 6144, 10, 1280, 128, 64, 64, 2);
    encode(fn, &m.wo1[i], 3, wo, 64, 6144, 10, 1280, 128, 64, 64, 1);
    p.k[i] = (const uint8_t*)k; p.v[i] = (const uint8_t*)v;
  }
  encode(fn, &m.out, 2, d_out, 1280, 1024, 1, 2560, 0, 64, 64, 1);
  const int stride = sms / kNumOp, n_att = sms - kNumOp, mul = (n_att % 37) ? 37 : 41;
  for (int c = 0, a = 0, n0 = 0, n1 = 0; c < kMaxCtas; c++) {
    int op = -1;
    if (sms == 132) {
      const int gpc = c < 64 ? (c >> 1) & 7 : (c < 120 ? 1 + ((c - 64) >> 1) % 7 : -1);
      if (gpc == 2) op = n0++;
      if (gpc == 5) op = 16 + n1++;
    } else if (c % stride == stride - 1 && c / stride < kNumOp) {
      op = c / stride;
    }
    p.first[c] = op >= 0 ? op : kNumOp + (a++ * mul) % n_att;
  }
  fused_kernel<<<sms, kThreads, kSmemBytes, cudaStreamPerThread>>>(m, p);
}
```
